```python
import torch

def _softmax(x, axis=-1):
    return torch.softmax(x, dim=axis)
def _gelu(x):
    return torch.nn.functional.gelu(x, approximate="tanh")
def _silu(x):
    return torch.nn.functional.silu(x)
def _sigmoid(x):
    return torch.sigmoid(x)
def _layernorm(x, axis=-1, eps=1e-5):
    m = x.mean(dim=axis, keepdim=True)
    v = x.var(dim=axis, keepdim=True, unbiased=False)
    return (x - m) / torch.sqrt(v + eps)
def _scatter_add(tgt, idx, src, axis=0):
    return tgt.clone().index_add_(axis, idx, src)
def _segment_sum(src, seg, n):
    out = torch.zeros((n,) + src.shape[1:], dtype=src.dtype)
    return out.index_add_(0, seg, src)
def _pad(x, pw):
    flat = tuple(v for pair in reversed(pw) for v in pair)
    return torch.nn.functional.pad(x, flat)

kernel_name = 'concat_heads__gqa_block_cached__mha_block_cached__near_ridge'

def setup_inputs():

    _w = (lambda a: (lambda t: t.to(torch.bfloat16) if t.is_floating_point() else t)(torch.as_tensor(a)))
    def _A_setup():
        B, Sq, D = 32, 48, 512
        Hq, Hkv, Sk, Dh = 32, 8, 512, 128
        assert Hq % Hkv == 0, (Hq, Hkv)
        return {
            "x": _w((lambda *s: torch.randn(*s, dtype=torch.bfloat16) * 0.8)(B, Sq, D)),
            "k_cache": _w((lambda *s: torch.randn(*s, dtype=torch.bfloat16) * 0.8)(B, Hkv, Sk, Dh)),
            "v_cache": _w((lambda *s: torch.randn(*s, dtype=torch.bfloat16) * 0.05)(B, Hkv, Sk, Dh)),
            "wq": _w((lambda *s: torch.randn(*s, dtype=torch.bfloat16) * 0.8)(D, Hq * Dh) * (D ** -0.5)),
            "wo": _w((lambda *s: torch.randn(*s, dtype=torch.bfloat16) * 0.05)(Hq * Dh, D) * ((Hq * Dh) ** -0.5)),
        }
    _A_in = _A_setup()

    def _B_setup():
        B, Sq, D = 32, 48, 512
        H, Sk, Dh = 32, 512, 128
        return {
            "x": _w((lambda *s: torch.randn(*s, dtype=torch.bfloat16) * 0.8)(B, Sq, D)),
            "k_cache": _w((lambda *s: torch.randn(*s, dtype=torch.bfloat16) * 0.8)(B, H, Sk, Dh)),
            "v_cache": _w((lambda *s: torch.randn(*s, dtype=torch.bfloat16) * 0.05)(B, H, Sk, Dh)),
            "wq": _w((lambda *s: torch.randn(*s, dtype=torch.bfloat16) * 0.8)(D, H * Dh) * (D ** -0.5)),
            "wo": _w((lambda *s: torch.randn(*s, dtype=torch.bfloat16) * 0.05)(H * Dh, D) * ((H * Dh) ** -0.5)),
        }
    _B_in = _B_setup()

    return {
        "A_x": _A_in["x"],
        "A_k_cache": _A_in["k_cache"],
        "A_v_cache": _A_in["v_cache"],
        "A_wq": _A_in["wq"],
        "A_wo": _A_in["wo"],
        "B_x": _B_in["x"],
        "B_k_cache": _B_in["k_cache"],
        "B_v_cache": _B_in["v_cache"],
        "B_wq": _B_in["wq"],
        "B_wo": _B_in["wo"],
    }

def reference(A_x, A_k_cache, A_v_cache, A_wq, A_wo, B_x, B_k_cache, B_v_cache, B_wq, B_wo):
    def _A_ref(x, k_cache, v_cache, wq, wo):
        B, Sq, D = x.shape
        Hq, Dh = 32, 128
        Hkv = k_cache.shape[1]
        rep = Hq // Hkv
        q = (lambda x, *d: x.permute(*d))((x @ wq).reshape(B, Sq, Hq, Dh), 0, 2, 1, 3)
        k = (lambda x, n, axis: torch.repeat_interleave(x, n, dim=axis))(k_cache, rep, axis=1)
        v = (lambda x, n, axis: torch.repeat_interleave(x, n, dim=axis))(v_cache, rep, axis=1)
        scores = torch.einsum("bhqd,bhkd->bhqk", q, k) * (Dh ** -0.5)
        p = _softmax(scores, axis=-1)
        o = torch.einsum("bhqk,bhkd->bhqd", p, v)
        return (lambda x, *d: x.permute(*d))(o, 0, 2, 1, 3).reshape(B, Sq, Hq * Dh) @ wo

    def _B_ref(x, k_cache, v_cache, wq, wo):
        B, Sq, D = x.shape
        H, Dh = 32, 128
        q = (lambda x, *d: x.permute(*d))((x @ wq).reshape(B, Sq, H, Dh), 0, 2, 1, 3)
        scores = torch.einsum("bhqd,bhkd->bhqk", q, k_cache) * (Dh ** -0.5)
        p = _softmax(scores, axis=-1)
        o = torch.einsum("bhqk,bhkd->bhqd", p, v_cache)
        return (lambda x, *d: x.permute(*d))(o, 0, 2, 1, 3).reshape(B, Sq, H * Dh) @ wo

    a = _A_ref(A_x, A_k_cache, A_v_cache, A_wq, A_wo)
    b = _B_ref(B_x, B_k_cache, B_v_cache, B_wq, B_wo)
    return torch.concatenate([a, b], axis=-1)
```

```cpp
#include <cuda_runtime.h>
#include <cuda_bf16.h>
#include <cuda.h>
#include <stdint.h>

#define TOKMODE 1

namespace {

constexpr int NB = 32, SQ = 48, DM = 512, NH = 32, SK = 512, DH = 128;
constexpr int NTOK = NB * SQ;
constexpr int RSA = 4;
constexpr int RSB = 8;
constexpr int SCR_B0 = RSA * 512;
constexpr int SCR_COLS = SCR_B0 + RSB * 128;
constexpr int NSLOT = 5;
constexpr int SLOT_BYTES = 34816;
constexpr int QBUF_BYTES = 49152;
constexpr int MB = 4;
constexpr int NT_MAX = 1576;

enum : uint32_t { T_QP = 0, T_MHA = 1, T_GQA = 2, T_OWN = 3, T_FIN = 4, T_END = 5 };

enum { M_KA, M_VA, M_KB, M_VB, M_XA, M_XB3, M_XB1, M_WQA, M_WQB, M_WOA, M_WOB, M_WOF, M_SA, M_SQ, M_SQ16, M_COUNT };

struct Params {
    CUtensorMap maps[M_COUNT];
    __nv_bfloat16* out;
    uint32_t nt;
    int grab;
    int dbg;
    uint16_t table[NT_MAX];
};

constexpr int F_QF = 0;
constexpr int F_OFA = 64;
constexpr int F_RFA = 128;
constexpr int F_OFB = 192;
constexpr int F_RFB = 448;
constexpr int F_AF = 704;
constexpr int F_FB = 720;
constexpr int F_COUNT = 752;

__device__ __align__(1024) __nv_bfloat16 g_scr[NTOK * SCR_COLS];
__device__ __align__(1024) float g_acc[8 * 2 * 192 * 256];
__device__ __align__(128) unsigned int g_flags[F_COUNT * 8];
__device__ __align__(128) unsigned int g_task_ctr[32];
__device__ __align__(128) unsigned long long g_ticket[16];
#define PROF(cond, k) do {} while (0)
#define TRACE(k) do {} while (0)

constexpr int OFF_Q = 0;
constexpr int OFF_RING = QBUF_BYTES;
constexpr int OFF_BAR = OFF_RING + NSLOT * SLOT_BYTES;
constexpr int B_FULL_SH = 0;
constexpr int B_FULL_PV = 5;
constexpr int B_EMPTY = 20;
constexpr int B_QFULL_PV = 25;
constexpr int B_QEMPTY = 29;
constexpr int B_GRANT = 32;
constexpr int B_MBFULL = 36;
constexpr int B_MBEMPTY = 40;
constexpr int B_DONE = 44;
constexpr int B_SETUP = 48;
constexpr int B_WANT = 49;
constexpr int OFF_MBOX = OFF_BAR + 512;
constexpr int OFF_TABLE = OFF_MBOX + 64;
constexpr int SMEM_BYTES = OFF_TABLE + NT_MAX * 2 + 1024;

constexpr uint32_t DH128 = (1024u >> 4) | (1u << 30);
constexpr uint32_t DH64 = (512u >> 4) | (2u << 30);

__device__ __forceinline__ uint32_t smem_u32(const void* p) { return (uint32_t)__cvta_generic_to_shared(p); }
__device__ __forceinline__ void mbar_init(uint32_t a, uint32_t c) { asm volatile("mbarrier.init.shared::cta.b64 [%0], %1;" ::"r"(a), "r"(c)); }
__device__ __forceinline__ void mbar_expect(uint32_t a, uint32_t bytes) { asm volatile("mbarrier.arrive.expect_tx.shared::cta.b64 _, [%0], %1;" ::"r"(a), "r"(bytes) : "memory"); }
__device__ __forceinline__ void mbar_arrive(uint32_t a) { asm volatile("mbarrier.arrive.shared::cta.b64 _, [%0];" ::"r"(a) : "memory"); }
__device__ __forceinline__ void mbar_arrive_n(uint32_t a, uint32_t n) { asm volatile("mbarrier.arrive.shared::cta.b64 _, [%0], %1;" ::"r"(a), "r"(n) : "memory"); }
__device__ __forceinline__ bool mbar_try(uint32_t a, uint32_t parity) {
    uint32_t ok;
    asm volatile("{\n.reg .pred p;\nmbarrier.try_wait.parity.shared::cta.b64 p, [%1], %2;\nselp.u32 %0, 1, 0, p;\n}\n" : "=r"(ok) : "r"(a), "r"(parity) : "memory");
    return ok != 0;
}
__device__ __forceinline__ bool mbar_test(uint32_t a, uint32_t parity) {
    uint32_t ok;
    asm volatile("{\n.reg .pred p;\nmbarrier.test_wait.parity.shared::cta.b64 p, [%1], %2;\nselp.u32 %0, 1, 0, p;\n}\n" : "=r"(ok) : "r"(a), "r"(parity) : "memory");
    return ok != 0;
}
__device__ __forceinline__ void mbar_wait(uint32_t a, uint32_t parity) {
    uint32_t n = 0;
    while (!mbar_try(a, parity)) { if (++n > (1u << 22)) __trap(); }
}
__device__ __forceinline__ void mbar_wait_c(uint32_t a, uint32_t parity) {
    while (!mbar_try(a, parity)) {}
}
__device__ __forceinline__ void tma2d(uint32_t dst, const CUtensorMap* m, int c0, int c1, uint32_t bar) {
    asm volatile("cp.async.bulk.tensor.2d.shared::cluster.global.mbarrier::complete_tx::bytes [%0], [%1, {%3, %4}], [%2];"
                 ::"r"(dst), "l"(m), "r"(bar), "r"(c0), "r"(c1) : "memory");
}
__device__ __forceinline__ void tma3d(uint32_t dst, const CUtensorMap* m, int c1, int c2, uint32_t bar) {
    asm volatile("cp.async.bulk.tensor.3d.shared::cluster.global.mbarrier::complete_tx::bytes [%0], [%1, {%3, %4, %5}], [%2];"
                 ::"r"(dst), "l"(m), "r"(bar), "r"(0), "r"(c1), "r"(c2) : "memory");
}
__device__ __forceinline__ void tma5d(uint32_t dst, const CUtensorMap* m, int c0, int c2, int c4, uint32_t bar) {
    asm volatile("cp.async.bulk.tensor.5d.shared::cluster.global.mbarrier::complete_tx::bytes [%0], [%1, {%4, %3, %5, %3, %6}], [%2];"
                 ::"r"(dst), "l"(m), "r"(bar), "r"(0), "r"(c0), "r"(c2), "r"(c4) : "memory");
}
__device__ __forceinline__ void tma3d_stream(uint32_t dst, const CUtensorMap* m, int c1, uint32_t bar, uint64_t pol) {
    asm volatile("cp.async.bulk.tensor.3d.shared::cluster.global.mbarrier::complete_tx::bytes.L2::cache_hint [%0], [%1, {%3, %4, %3}], [%2], %5;"
                 ::"r"(dst), "l"(m), "r"(bar), "r"(0), "r"(c1), "l"(pol) : "memory");
}
__device__ __forceinline__ uint32_t tri_pos(int i) {
    if (i < 3) return i << 3;
    if (i >= 21) return ((i - 21) << 3) | 7;
    const int v = i - 3, j = (v * 43) >> 8, c = v - 6 * j;
    return ((c >> 1) << 3) | (2 * j + 1 + (c & 1));
}
__device__ __forceinline__ void fence_proxy_async_global() { asm volatile("fence.proxy.async.global;" ::: "memory"); }
__device__ __forceinline__ void poll_flag(int idx, uint32_t target, bool eager = false) {
    const unsigned int* p = &g_flags[idx * 8];
    uint32_t n = 0;
    while (true) {
        uint32_t v;
        asm volatile("ld.acquire.gpu.global.u32 %0, [%1];" : "=r"(v) : "l"(p) : "memory");
        if ((int32_t)(v - target) >= 0) break;
        do {
            if (++n > (1u << 21)) __trap();
            __nanosleep(64);
            if (eager) break;
            asm volatile("ld.relaxed.gpu.global.u32 %0, [%1];" : "=r"(v) : "l"(p) : "memory");
        } while ((int32_t)(v - target) < 0);
    }
}
__device__ __forceinline__ void flag_add(int idx) {
    asm volatile("red.relaxed.gpu.global.add.u32 [%0], 1;" ::"l"(&g_flags[idx * 8]) : "memory");
}
__device__ __forceinline__ void wg_fence() { asm volatile("wgmma.fence.sync.aligned;" ::: "memory"); }
__device__ __forceinline__ void wg_commit() { asm volatile("wgmma.commit_group.sync.aligned;" ::: "memory"); }
template <int N> __device__ __forceinline__ void wg_wait() { asm volatile("wgmma.wait_group.sync.aligned %0;" ::"n"(N) : "memory"); }
template <int N> __device__ __forceinline__ void reg_fence(float (&d)[N]) {
#pragma unroll
    for (int i = 0; i < N; i++) asm volatile("" : "+f"(d[i])::"memory");
}
__device__ __forceinline__ void nbar_sync(uint32_t id, uint32_t n) { asm volatile("barrier.cta.sync %0, %1;" ::"r"(id), "r"(n) : "memory"); }
__device__ __forceinline__ void nbar_arrive(uint32_t id, uint32_t n) { asm volatile("barrier.cta.arrive %0, %1;" ::"r"(id), "r"(n) : "memory"); }
__device__ __forceinline__ uint32_t dlo(uint32_t addr, uint32_t lbo) { return (addr >> 4) | ((lbo >> 4) << 16); }
__device__ __forceinline__ uint32_t pack_bf16(float lo, float hi) {
    uint32_t r;
    asm("cvt.rn.bf16x2.f32 %0, %1, %2;" : "=r"(r) : "f"(hi), "f"(lo));
    return r;
}
__device__ __forceinline__ float ex2(float x) { float y; asm("ex2.approx.ftz.f32 %0, %1;" : "=f"(y) : "f"(x)); return y; }
__device__ __forceinline__ uint32_t wrap5(uint32_t s) { return s >= NSLOT ? s - NSLOT : s; }
__device__ __forceinline__ uint4 quad_transpose(uint32_t v0, uint32_t v1, uint32_t v2, uint32_t v3, int t) {
    const bool o1 = t & 1, o2 = t & 2;
    uint32_t s0 = __shfl_xor_sync(0xffffffffu, o1 ? v0 : v1, 1);
    uint32_t s1 = __shfl_xor_sync(0xffffffffu, o1 ? v2 : v3, 1);
    uint32_t a0 = o1 ? s0 : v0, a1 = o1 ? v1 : s0, b0 = o1 ? s1 : v2, b1 = o1 ? v3 : s1;
    uint32_t r0 = __shfl_xor_sync(0xffffffffu, o2 ? a0 : b0, 2);
    uint32_t r1 = __shfl_xor_sync(0xffffffffu, o2 ? a1 : b1, 2);
    uint4 o;
    o.x = o2 ? r0 : a0; o.y = o2 ? r1 : a1; o.z = o2 ? b0 : r0; o.w = o2 ? b1 : r1;
    return o;
}
__device__ __forceinline__ void store_frag(const float (&d)[64], float s0, float s1, __nv_bfloat16* p, int ld, int t) {
#pragma unroll
    for (int j = 0; j < 16; j += 4) {
        uint4 lo = quad_transpose(pack_bf16(d[4 * j] * s0, d[4 * j + 1] * s0), pack_bf16(d[4 * j + 4] * s0, d[4 * j + 5] * s0),
                                  pack_bf16(d[4 * j + 8] * s0, d[4 * j + 9] * s0), pack_bf16(d[4 * j + 12] * s0, d[4 * j + 13] * s0), t);
        uint4 hi = quad_transpose(pack_bf16(d[4 * j + 2] * s1, d[4 * j + 3] * s1), pack_bf16(d[4 * j + 6] * s1, d[4 * j + 7] * s1),
                                  pack_bf16(d[4 * j + 10] * s1, d[4 * j + 11] * s1), pack_bf16(d[4 * j + 14] * s1, d[4 * j + 15] * s1), t);
        *reinterpret_cast<uint4*>(p + 8 * j) = lo;
        *reinterpret_cast<uint4*>(p + 8 * j + 8 * ld) = hi;
    }
}
__device__ __forceinline__ void store_frag_perm(const float (&d)[64], float s0, float s1, __nv_bfloat16* p, int ld) {
#pragma unroll
    for (int j = 0; j < 16; j += 4) {
        *reinterpret_cast<uint4*>(p + 8 * j) = make_uint4(pack_bf16(d[4 * j] * s0, d[4 * j + 1] * s0), pack_bf16(d[4 * j + 4] * s0, d[4 * j + 5] * s0),
                                                          pack_bf16(d[4 * j + 8] * s0, d[4 * j + 9] * s0), pack_bf16(d[4 * j + 12] * s0, d[4 * j + 13] * s0));
        *reinterpret_cast<uint4*>(p + 8 * j + 8 * ld) = make_uint4(pack_bf16(d[4 * j + 2] * s1, d[4 * j + 3] * s1), pack_bf16(d[4 * j + 6] * s1, d[4 * j + 7] * s1),
                                                                   pack_bf16(d[4 * j + 10] * s1, d[4 * j + 11] * s1), pack_bf16(d[4 * j + 14] * s1, d[4 * j + 15] * s1));
    }
}
__device__ __forceinline__ void acc_store(const float (&d)[64], float* ap) {
#pragma unroll
    for (int j = 0; j < 16; j++) *reinterpret_cast<float4*>(ap + j * 128) = make_float4(d[4 * j], d[4 * j + 1], d[4 * j + 2], d[4 * j + 3]);
}

template <uint32_t AH, uint32_t BH>
__device__ __forceinline__ void wgmma_ss(float (&d)[64], uint32_t da, uint32_t db) {
    asm volatile("{\n.reg .pred p;\n.reg .b64 a, b;\n.reg .b32 x, y;\nsetp.eq.b32 p, 0, 0;\nmov.b32 x, %66;\nmov.b32 y, %67;\nmov.b64 a, {%64, x};\nmov.b64 b, {%65, y};\n"
        "wgmma.mma_async.sync.aligned.m64n128k16.f32.bf16.bf16 "
        "{%0, %1, %2, %3, %4, %5, %6, %7, %8, %9, %10, %11, %12, %13, %14, %15, %16, %17, %18, %19, %20, %21, %22, %23, "
        "%24, %25, %26, %27, %28, %29, %30, %31, %32, %33, %34, %35, %36, %37, %38, %39, %40, %41, %42, %43, %44, %45, "
        "%46, %47, %48, %49, %50, %51, %52, %53, %54, %55, %56, %57, %58, %59, %60, %61, %62, %63}, "
        "a, b, p, 1, 1, 0, 0;\n}\n"
        : "+f"(d[0]), "+f"(d[1]), "+f"(d[2]), "+f"(d[3]), "+f"(d[4]), "+f"(d[5]), "+f"(d[6]), "+f"(d[7]), "+f"(d[8]),
          "+f"(d[9]), "+f"(d[10]), "+f"(d[11]), "+f"(d[12]), "+f"(d[13]), "+f"(d[14]), "+f"(d[15]), "+f"(d[16]),
          "+f"(d[17]), "+f"(d[18]), "+f"(d[19]), "+f"(d[20]), "+f"(d[21]), "+f"(d[22]), "+f"(d[23]), "+f"(d[24]),
          "+f"(d[25]), "+f"(d[26]), "+f"(d[27]), "+f"(d[28]), "+f"(d[29]), "+f"(d[30]), "+f"(d[31]), "+f"(d[32]),
          "+f"(d[33]), "+f"(d[34]), "+f"(d[35]), "+f"(d[36]), "+f"(d[37]), "+f"(d[38]), "+f"(d[39]), "+f"(d[40]),
          "+f"(d[41]), "+f"(d[42]), "+f"(d[43]), "+f"(d[44]), "+f"(d[45]), "+f"(d[46]), "+f"(d[47]), "+f"(d[48]),
          "+f"(d[49]), "+f"(d[50]), "+f"(d[51]), "+f"(d[52]), "+f"(d[53]), "+f"(d[54]), "+f"(d[55]), "+f"(d[56]),
          "+f"(d[57]), "+f"(d[58]), "+f"(d[59]), "+f"(d[60]), "+f"(d[61]), "+f"(d[62]), "+f"(d[63])
        : "r"(da), "r"(db), "n"(AH), "n"(BH));
}

template <uint32_t AH, uint32_t BH>
__device__ __forceinline__ void wgmma_ss_first(float (&d)[64], uint32_t da, uint32_t db) {
    asm volatile("{\n.reg .pred p;\n.reg .b64 a, b;\n.reg .b32 x, y;\nsetp.ne.b32 p, 0, 0;\nmov.b32 x, %66;\nmov.b32 y, %67;\nmov.b64 a, {%64, x};\nmov.b64 b, {%65, y};\n"
        "wgmma.mma_async.sync.aligned.m64n128k16.f32.bf16.bf16 "
        "{%0, %1, %2, %3, %4, %5, %6, %7, %8, %9, %10, %11, %12, %13, %14, %15, %16, %17, %18, %19, %20, %21, %22, %23, "
        "%24, %25, %26, %27, %28, %29, %30, %31, %32, %33, %34, %35, %36, %37, %38, %39, %40, %41, %42, %43, %44, %45, "
        "%46, %47, %48, %49, %50, %51, %52, %53, %54, %55, %56, %57, %58, %59, %60, %61, %62, %63}, "
        "a, b, p, 1, 1, 0, 0;\n}\n"
        : "=f"(d[0]), "=f"(d[1]), "=f"(d[2]), "=f"(d[3]), "=f"(d[4]), "=f"(d[5]), "=f"(d[6]), "=f"(d[7]), "=f"(d[8]),
          "=f"(d[9]), "=f"(d[10]), "=f"(d[11]), "=f"(d[12]), "=f"(d[13]), "=f"(d[14]), "=f"(d[15]), "=f"(d[16]),
          "=f"(d[17]), "=f"(d[18]), "=f"(d[19]), "=f"(d[20]), "=f"(d[21]), "=f"(d[22]), "=f"(d[23]), "=f"(d[24]),
          "=f"(d[25]), "=f"(d[26]), "=f"(d[27]), "=f"(d[28]), "=f"(d[29]), "=f"(d[30]), "=f"(d[31]), "=f"(d[32]),
          "=f"(d[33]), "=f"(d[34]), "=f"(d[35]), "=f"(d[36]), "=f"(d[37]), "=f"(d[38]), "=f"(d[39]), "=f"(d[40]),
          "=f"(d[41]), "=f"(d[42]), "=f"(d[43]), "=f"(d[44]), "=f"(d[45]), "=f"(d[46]), "=f"(d[47]), "=f"(d[48]),
          "=f"(d[49]), "=f"(d[50]), "=f"(d[51]), "=f"(d[52]), "=f"(d[53]), "=f"(d[54]), "=f"(d[55]), "=f"(d[56]),
          "=f"(d[57]), "=f"(d[58]), "=f"(d[59]), "=f"(d[60]), "=f"(d[61]), "=f"(d[62]), "=f"(d[63])
        : "r"(da), "r"(db), "n"(AH), "n"(BH));
}

template <uint32_t AH, uint32_t BH>
__device__ __forceinline__ void wgmma_ss_tb(float (&d)[64], uint32_t da, uint32_t db) {
    asm volatile("{\n.reg .pred p;\n.reg .b64 a, b;\n.reg .b32 x, y;\nsetp.eq.b32 p, 0, 0;\nmov.b32 x, %66;\nmov.b32 y, %67;\nmov.b64 a, {%64, x};\nmov.b64 b, {%65, y};\n"
        "wgmma.mma_async.sync.aligned.m64n128k16.f32.bf16.bf16 "
        "{%0, %1, %2, %3, %4, %5, %6, %7, %8, %9, %10, %11, %12, %13, %14, %15, %16, %17, %18, %19, %20, %21, %22, %23, "
        "%24, %25, %26, %27, %28, %29, %30, %31, %32, %33, %34, %35, %36, %37, %38, %39, %40, %41, %42, %43, %44, %45, "
        "%46, %47, %48, %49, %50, %51, %52, %53, %54, %55, %56, %57, %58, %59, %60, %61, %62, %63}, "
        "a, b, p, 1, 1, 0, 1;\n}\n"
        : "+f"(d[0]), "+f"(d[1]), "+f"(d[2]), "+f"(d[3]), "+f"(d[4]), "+f"(d[5]), "+f"(d[6]), "+f"(d[7]), "+f"(d[8]),
          "+f"(d[9]), "+f"(d[10]), "+f"(d[11]), "+f"(d[12]), "+f"(d[13]), "+f"(d[14]), "+f"(d[15]), "+f"(d[16]),
          "+f"(d[17]), "+f"(d[18]), "+f"(d[19]), "+f"(d[20]), "+f"(d[21]), "+f"(d[22]), "+f"(d[23]), "+f"(d[24]),
          "+f"(d[25]), "+f"(d[26]), "+f"(d[27]), "+f"(d[28]), "+f"(d[29]), "+f"(d[30]), "+f"(d[31]), "+f"(d[32]),
          "+f"(d[33]), "+f"(d[34]), "+f"(d[35]), "+f"(d[36]), "+f"(d[37]), "+f"(d[38]), "+f"(d[39]), "+f"(d[40]),
          "+f"(d[41]), "+f"(d[42]), "+f"(d[43]), "+f"(d[44]), "+f"(d[45]), "+f"(d[46]), "+f"(d[47]), "+f"(d[48]),
          "+f"(d[49]), "+f"(d[50]), "+f"(d[51]), "+f"(d[52]), "+f"(d[53]), "+f"(d[54]), "+f"(d[55]), "+f"(d[56]),
          "+f"(d[57]), "+f"(d[58]), "+f"(d[59]), "+f"(d[60]), "+f"(d[61]), "+f"(d[62]), "+f"(d[63])
        : "r"(da), "r"(db), "n"(AH), "n"(BH));
}

template <uint32_t BH>
__device__ __forceinline__ void wgmma_rs_tb(float (&d)[64], uint32_t a0, uint32_t a1, uint32_t a2, uint32_t a3, uint32_t db) {
    asm volatile("{\n.reg .pred p;\n.reg .b64 b;\n.reg .b32 y;\nsetp.eq.b32 p, 0, 0;\nmov.b32 y, %69;\nmov.b64 b, {%68, y};\n"
        "wgmma.mma_async.sync.aligned.m64n128k16.f32.bf16.bf16 "
        "{%0, %1, %2, %3, %4, %5, %6, %7, %8, %9, %10, %11, %12, %13, %14, %15, %16, %17, %18, %19, %20, %21, %22, %23, "
        "%24, %25, %26, %27, %28, %29, %30, %31, %32, %33, %34, %35, %36, %37, %38, %39, %40, %41, %42, %43, %44, %45, "
        "%46, %47, %48, %49, %50, %51, %52, %53, %54, %55, %56, %57, %58, %59, %60, %61, %62, %63}, "
        "{%64, %65, %66, %67}, b, p, 1, 1, 1;\n}\n"
        : "+f"(d[0]), "+f"(d[1]), "+f"(d[2]), "+f"(d[3]), "+f"(d[4]), "+f"(d[5]), "+f"(d[6]), "+f"(d[7]), "+f"(d[8]),
          "+f"(d[9]), "+f"(d[10]), "+f"(d[11]), "+f"(d[12]), "+f"(d[13]), "+f"(d[14]), "+f"(d[15]), "+f"(d[16]),
          "+f"(d[17]), "+f"(d[18]), "+f"(d[19]), "+f"(d[20]), "+f"(d[21]), "+f"(d[22]), "+f"(d[23]), "+f"(d[24]),
          "+f"(d[25]), "+f"(d[26]), "+f"(d[27]), "+f"(d[28]), "+f"(d[29]), "+f"(d[30]), "+f"(d[31]), "+f"(d[32]),
          "+f"(d[33]), "+f"(d[34]), "+f"(d[35]), "+f"(d[36]), "+f"(d[37]), "+f"(d[38]), "+f"(d[39]), "+f"(d[40]),
          "+f"(d[41]), "+f"(d[42]), "+f"(d[43]), "+f"(d[44]), "+f"(d[45]), "+f"(d[46]), "+f"(d[47]), "+f"(d[48]),
          "+f"(d[49]), "+f"(d[50]), "+f"(d[51]), "+f"(d[52]), "+f"(d[53]), "+f"(d[54]), "+f"(d[55]), "+f"(d[56]),
          "+f"(d[57]), "+f"(d[58]), "+f"(d[59]), "+f"(d[60]), "+f"(d[61]), "+f"(d[62]), "+f"(d[63])
        : "r"(a0), "r"(a1), "r"(a2), "r"(a3), "r"(db), "n"(BH));
}

__global__ void __launch_bounds__(512, 1) fused_attn_kernel(const __grid_constant__ Params P) {
    extern __shared__ uint8_t smem_raw[];
    const uint32_t sb = (smem_u32(smem_raw) + 1023u) & ~1023u;
    uint8_t* sgen = smem_raw + (sb - smem_u32(smem_raw));
    const uint32_t bar = sb + OFF_BAR;
    volatile uint32_t* mbox = reinterpret_cast<volatile uint32_t*>(sgen + OFF_MBOX);
    const int warp = __shfl_sync(0xffffffffu, threadIdx.x >> 5, 0), lane = threadIdx.x & 31;

    if (threadIdx.x == 0) {
        for (int i = 0; i < 20; i++) mbar_init(bar + 8 * (B_FULL_SH + i), 1);
        for (int i = 0; i < 5; i++) mbar_init(bar + 8 * (B_EMPTY + i), 12);
        for (int i = 0; i < 3; i++) mbar_init(bar + 8 * (B_QFULL_PV + i), 1);
        for (int i = 0; i < 3; i++) mbar_init(bar + 8 * (B_QEMPTY + i), 4);
        for (int i = 0; i < MB; i++) {
            mbar_init(bar + 8 * (B_MBFULL + i), 1);
            mbar_init(bar + 8 * (B_MBEMPTY + i), 15);
            mbar_init(bar + 8 * (B_DONE + i), 12);
            mbar_init(bar + 8 * (B_GRANT + i), 1);
        }
        mbar_init(bar + 8 * B_SETUP, 1);
        mbar_init(bar + 8 * B_WANT, 1);
        mbox[9] = 0;
        asm volatile("fence.mbarrier_init.release.cluster;" ::: "memory");
        asm volatile("fence.proxy.async.shared::cta;" ::: "memory");
    }
    __syncthreads();

    if (warp >= 12) {
        asm volatile("setmaxnreg.dec.sync.aligned.u32 32;");
        if (warp == 12) {
            uint32_t word = P.table[blockIdx.x];
            if (lane == 0) {
                mbox[0] = word;
                mbar_arrive(bar + 8 * B_MBFULL);
            }
            {
                uint32_t* dst = reinterpret_cast<uint32_t*>(sgen + OFF_TABLE);
                const uint32_t* src = reinterpret_cast<const uint32_t*>(P.table);
                for (int i = lane; i < NT_MAX / 2; i += 32) dst[i] = src[i];
            }
            __syncwarp();
            if (lane == 0) {
                uint32_t rr = ((word & 0x4007) == T_MHA || (word & 7) == T_FIN) ? 1 : 0, mbs = 1 | 4, wph = 0;
                mbar_wait(bar + 8 * B_SETUP, 0);
                const uint32_t base = mbox[8] * P.nt - gridDim.x;
                do {
                    mbar_wait(bar + 8 * B_WANT, wph);
                    wph ^= 1;
                    uint32_t t;
                    asm volatile("atom.relaxed.gpu.global.add.u32 %0, [%1], 1;" : "=r"(t) : "l"(&g_task_ctr[0]) : "memory");
                    t -= base;
                    word = T_END;
                    if (t < P.nt) {
                        word = reinterpret_cast<const uint16_t*>(sgen + OFF_TABLE)[t];
                        if ((word & 0x4007) == T_MHA || (word & 7) == T_FIN) { word |= rr << 16; rr = (rr == 2) ? 0 : rr + 1; }
                    }
                    const uint32_t mbi = mbs & 3;
                    mbar_wait(bar + 8 * (B_MBEMPTY + mbi), mbs >> 2);
                    mbox[mbi] = word;
                    mbar_arrive(bar + 8 * (B_MBFULL + mbi));
                    mbs = (mbs + 1) & 7;
                } while (word != T_END);
            }
        } else if (warp == 13) {
            if (lane == 0) {
                const unsigned long long ticket = atomicAdd(&g_ticket[0], 1ull);
                const uint32_t e1 = (uint32_t)(ticket / gridDim.x) + 1;
                mbox[8] = e1 - 1;
                mbar_arrive(bar + 8 * B_SETUP);
                uint32_t mbs = 0, qeph = 7, tickets = 0;
                while (true) {
                    mbar_wait(bar + 8 * (B_MBFULL + (mbs & 3)), mbs >> 2);
                    const uint32_t word = mbox[mbs & 3];
                    mbar_arrive(bar + 8 * (B_MBEMPTY + (mbs & 3)));
                    const uint32_t grant = bar + 8 * (B_GRANT + (mbs & 3));
                    mbs = (mbs + 1) & 7;
                    const uint32_t type = word & 7, w = word >> 16;
                    if (type == T_END) break;
                    if (type == T_QP) {
                        const int g = (word >> 4) & 7, r = (word >> 8) & 7;
                        if (r >= RSA && !(P.dbg & 8)) poll_flag(F_RFA + (r - RSA) * 8 + g, 2 * e1);
                        mbar_arrive(grant);
                    } else if (type == T_OWN) {
                        mbar_arrive(grant);
                        const int f0 = ((word & 8) ? F_OFB : F_OFA) + ((word >> 4) & 7), nb = (word & 8) ? 28 : 8;
                        for (int k = 0; k < nb; k++) {
                            poll_flag(f0 + k * 8, 4 * e1);
                            tickets++;
                            asm volatile("st.release.cta.shared.u32 [%0], %1;" ::"r"(sb + OFF_MBOX + 36), "r"(tickets) : "memory");
                        }
                    } else if (type == T_MHA) {
                        const int b = (word >> 4) & 31, h = (word >> 9) & 31, cnt = (word & 0x4000) ? 3 : 1;
                        for (int k = 0; k < cnt; k++) {
                            const uint32_t wi = w + k;
                            mbar_wait(bar + 8 * (B_QEMPTY + wi), (qeph >> wi) & 1);
                            qeph ^= 1u << wi;
                            mbar_arrive(bar + 8 * (B_QFULL_PV + wi));
                        }
                        if (h >= RSB && !(P.dbg & 8)) {
                            poll_flag(F_RFB + (h - RSB) * 8 + (b >> 2), 2 * e1);
                            if (((b + cnt - 1) >> 2) != (b >> 2)) poll_flag(F_RFB + (h - RSB) * 8 + (b >> 2) + 1, 2 * e1);
                        }
                        mbar_arrive(grant);
                    } else if (type == T_GQA) {
                        const int b = (word >> 4) & 31, r = (word >> 9) & 7;
                        mbar_arrive(grant);
                        if (!(P.dbg & 1)) poll_flag(F_QF + r * 8 + (b >> 2), 2 * e1);
                        fence_proxy_async_global();
                        int c = (r % RSA) * 512, row = b * SQ;
                        for (int i = 0; i < 12; i++) {
                            const uint32_t f = bar + 8 * (B_QFULL_PV + (i >> 2));
                            if ((i & 3) == 0) { mbar_wait(bar + 8 * (B_QEMPTY + (i >> 2)), (qeph >> (i >> 2)) & 1); mbar_expect(f, 16384); }
                            tma2d(sb + OFF_Q + i * 2048, &P.maps[M_SQ16], c, row, f);
                            tma2d(sb + OFF_Q + 24576 + i * 2048, &P.maps[M_SQ16], c + 64, row, f);
                            row += 16;
                            if (row == b * SQ + SQ) { row = b * SQ; c += 128; }
                        }
                        qeph ^= 7;
                    } else {
                        const int b = (word >> 4) & 31;
                        poll_flag(F_AF + (b >> 2) * 2 + ((word >> 10) & 1), e1);
                        mbar_arrive(grant);
                        poll_flag(F_FB + b, 4 * e1, true);
                        const uint32_t f = bar + 8 * (B_QFULL_PV + w);
                        fence_proxy_async_global();
                        for (int i = 0; i < 3; i++) mbar_wait(bar + 8 * (B_QEMPTY + i), (qeph >> i) & 1);
                        qeph ^= 7;
                        mbar_expect(f, 49152);
                        for (int i = 0; i < 8; i++) tma2d(sb + OFF_Q + i * 6144, &P.maps[M_SQ], SCR_B0 + (28 % RSB) * 128 + i * 64, b * SQ, f);
                    }
                }
            }
        } else if (warp == 14) {
            if (lane == 0) {
                uint32_t mbs = 0;
                while (true) {
                    const uint32_t mbi = mbs & 3;
                    mbar_wait(bar + 8 * (B_MBFULL + mbi), mbs >> 2);
                    const uint32_t word = mbox[mbi];
                    const uint32_t type = word & 7;
                    if (type == T_END) break;
                    mbar_wait(bar + 8 * (B_DONE + mbi), mbs >> 2);
                    if (type != T_FIN && !(type == T_OWN && !(word & 8))) {
                        if (!(P.dbg & 32)) {
                        fence_proxy_async_global();
                        asm volatile("fence.acq_rel.gpu;" ::: "memory");
                        }
                        if (type == T_QP) flag_add(F_QF + ((word >> 8) & 7) * 8 + ((word >> 4) & 7));
                        else if (type == T_GQA) flag_add(F_OFA + ((word >> 9) & 7) * 8 + ((word >> 6) & 7));
                        else if (type == T_OWN) flag_add(F_AF + ((word >> 4) & 7) * 2 + ((word >> 7) & 1));
                        else {
                            const int b = (word >> 4) & 31, h = (word >> 9) & 31, cnt = (word & 0x4000) ? 3 : 1;
                            for (int k = 0; k < cnt; k++) flag_add(h >= 28 ? F_FB + b + k : F_OFB + h * 8 + ((b + k) >> 2));
                        }
                    }
                    mbar_arrive(bar + 8 * (B_MBEMPTY + mbi));
                    mbs = (mbs + 1) & 7;
                }
            }
        } else {
            uint64_t pol;
            asm volatile("createpolicy.fractional.L2::evict_first.b64 %0, 1.0;" : "=l"(pol));
            uint32_t seq = NSLOT, mbs = 0, tickets = 0;
            while (true) {
                mbar_wait(bar + 8 * (B_MBFULL + (mbs & 3)), mbs >> 2);
                const uint32_t word = __shfl_sync(0xffffffffu, mbox[mbs & 3], 0);
                if (lane == 0) mbar_arrive(bar + 8 * (B_MBEMPTY + (mbs & 3)));
                mbs = (mbs + 1) & 7;
                const uint32_t type = word & 7, br = (word >> 3) & 1;
                if (type == T_END) break;
                const bool tri = (word & 0x4000) != 0;
                const int n = type == T_QP ? 16 : type == T_OWN ? 16 : type == T_FIN ? 4 : type == T_GQA ? 8 : (tri ? 32 : 16);
                const int nchunk = type == T_OWN ? (br ? 7 : 8) : 1;
#pragma unroll 1
                for (int ch = 0; ch < nchunk; ch++) {
                    int ln = threadIdx.x & 31;
                    asm volatile("" : "+r"(ln));
                    const uint32_t pos = (seq + ln) % (2 * NSLOT);
                    const uint32_t slot = wrap5(pos), epar = pos >= NSLOT;
                    uint32_t fbar = B_FULL_SH, bytes = 32768, m0, m1 = 0;
                    int c1, c2 = 0, a0 = 0, a1 = 0;
                    if (type == T_QP || type == T_OWN) {
                        const int k = (ch * 16 + ln) * 32;
                        bytes = 28672; c1 = k; c2 = ((word >> 7) & 15) * 4; a1 = ((word >> 4) & 7) * 192;
                        if (type == T_QP) { m0 = M_WQA; m1 = M_XA; a0 = k; }
                        else { m0 = M_WOA + br; m1 = M_SA; c1 = k >> 3; a0 = br ? SCR_B0 + k % (RSB * 128) : k % SCR_B0; }
                    } else if (type == T_FIN) {
                        fbar = B_FULL_PV + 5 * (word >> 16); m0 = M_WOF; c1 = 0; c2 = (28 + ln) * 4; a0 = ((word >> 9) & 3) * 128;
                    } else if (type == T_GQA) {
                        m0 = M_KA + (ln & 1); c1 = (((word >> 4) & 31) * 8 + ((word >> 9) & 7)) * SK + (ln >> 1) * 128;
                    } else if (ln < 8) {
                        if (!tri) fbar = B_FULL_PV + 5 * (word >> 16);
                        bytes = tri ? 34816 : 22528; m0 = M_WQB; m1 = tri ? M_XB3 : M_XB1;
                        c1 = ln * 64; c2 = ((word >> 9) & 31) * 2; a0 = ln * 64; a1 = ((word >> 4) & 31) * SQ;
                    } else {
                        const uint32_t u = tri ? tri_pos(ln - 8) : ln - 8;
                        fbar = B_FULL_PV + 5 * (tri ? (u >> 3) : (word >> 16)); m0 = M_KB + (u & 1);
                        c1 = ((((word >> 4) & 31) + (u >> 3)) * 32 + ((word >> 9) & 31)) * SK + ((u & 7) >> 1) * 128;
                    }
                    fbar = bar + 8 * (fbar + slot);
                    const uint32_t ebar = bar + 8 * (B_EMPTY + slot), dst = sb + OFF_RING + slot * SLOT_BYTES;
                    const CUtensorMap* p0 = &P.maps[m0];
                    const CUtensorMap* p1 = &P.maps[m1];
                    const int want = (ch + 1 < nchunk || type == T_FIN || type == T_GQA) ? -1 : n - P.grab;
                    const uint32_t need = type != T_OWN ? 0 : tickets + 1 + (br ? (ln >> 2) : 0);
                    if (type == T_OWN) tickets += br ? 4 : 1;
#pragma unroll 1
                    for (int i = 0; i < n; i++) {
                        if (ln == i) {
                            if (need) {
                                uint32_t v, c = 0;
                                while (true) {
                                    asm volatile("ld.acquire.cta.shared.u32 %0, [%1];" : "=r"(v) : "r"(sb + OFF_MBOX + 36) : "memory");
                                    if (v >= need) break;
                                    if (++c > (1u << 23)) __trap();
                                    __nanosleep(32);
                                }
                                fence_proxy_async_global();
                            }
                            mbar_wait(ebar, epar);
                            if (m0 > M_VB && (P.dbg & 128)) bytes = 0;
                            mbar_expect(fbar, bytes);
                            if (m0 <= M_VB) tma3d_stream(dst, p0, c1, fbar, pol);
                            else if (bytes) {
                                if (m0 < M_WOA) tma3d(dst, p0, c1, c2, fbar);
                                else tma5d(dst, p0, m1 ? 0 : a0, c1, c2, fbar);
                                if (m1) tma2d(dst + 16384, p1, a0, a1, fbar);
                                else tma5d(dst + 16384, p0, a0 + 64, c1, c2, fbar);
                            }
                            if (i == want) mbar_arrive(bar + 8 * B_WANT);
                        }
                        __syncwarp();
                    }
                    if (type == T_GQA && ln == 8) { mbar_wait(ebar, epar); mbar_arrive(bar + 8 * B_WANT); }
                    if (type == T_FIN && ln == 8) { mbar_wait(ebar, epar); mbar_arrive(bar + 8 * B_WANT); }
                    __syncwarp();
                    seq = (seq + n) % (2 * NSLOT);
                }
            }
        }
    } else {
        asm volatile("setmaxnreg.inc.sync.aligned.u32 160;");
        const uint32_t w = warp >> 2, wq = warp & 3;
        uint32_t st = 0;
        const uint32_t ring = sb + OFF_RING;
#define MB_ADDR(base) (bar + 8 * (base) + ((st >> 13) & 24))
#define MB_PAR ((st >> 18) & 1)
#define DONE_BAR MB_ADDR(B_DONE)
#define WAIT_GRANT() mbar_wait_c(MB_ADDR(B_GRANT), MB_PAR)
#define SET_SLOT(x) st = (st & ~(7u << 20)) | ((x) << 20)
        for (;; st = (st & ~(7u << 16)) | ((st + (1u << 16)) & (7u << 16))) {
            asm volatile("" : "+r"(st));
            mbar_wait_c(MB_ADDR(B_MBFULL), MB_PAR);
            const uint32_t word = __shfl_sync(0xffffffffu, mbox[(st >> 16) & 3], 0);
            if (lane == 0) mbar_arrive(MB_ADDR(B_MBEMPTY));
            uint32_t slot = st >> 20;
            const uint32_t type = word & 7;
            if (type == T_END) break;
#define LANE_IDS() int ln = threadIdx.x & 31; asm volatile("" : "+r"(ln)); const int g8 = ln >> 2, t4 = ln & 3; (void)g8; (void)t4

            if (type == T_QP || type == T_OWN) {
                float acc0[64], acc1[64];
#pragma unroll
                for (int i = 0; i < 64; i++) { acc0[i] = 0.f; acc1[i] = 0.f; }
                const uint32_t br = (word >> 3) & 1, g = (word >> 4) & 7, nh = (word >> 7) & 1;
                const int n = type == T_QP ? 16 : (br ? 112 : 128);
                const uint32_t bmask = br ? 3 : 15;
                uint32_t prev = 0;
#pragma unroll 1
                for (int i = 0; i < n; i++) {
                    mbar_wait_c(bar + 8 * (B_FULL_SH + slot), (st >> slot) & 1);
                    st ^= 1u << slot;
                    PROF(i == 0 && threadIdx.x == 0, 1);
                    const uint32_t s = ring + slot * SLOT_BYTES;
                    const uint32_t da = dlo(s + 16384 + w * 4096, 16), db = dlo(s, 4096);
                    wg_fence();
                    wgmma_ss_tb<DH64, DH128>(acc0, da, db);
                    wgmma_ss_tb<DH64, DH128>(acc1, da, db + 512);
                    wgmma_ss_tb<DH64, DH128>(acc0, da + 2, db + 128);
                    wgmma_ss_tb<DH64, DH128>(acc1, da + 2, db + 640);
                    wg_commit();
                    if (type == T_OWN && (i & bmask) == bmask && threadIdx.x == 0) flag_add((br ? F_RFB + (i >> 2) * 8 : F_RFA + (i >> 4) * 8) + g);
                    if (i > 0) {
                        wg_wait<1>();
                        if (lane == 0) mbar_arrive(bar + 8 * (B_EMPTY + prev));
                    }
                    prev = slot;
                    slot = wrap5(slot + 1);
                }
                wg_wait<0>();
                reg_fence(acc0);
                reg_fence(acc1);
                SET_SLOT(slot);
                asm volatile("" : "+r"(st));
                if (lane == 0) mbar_arrive(bar + 8 * (B_EMPTY + prev));
                PROF(threadIdx.x == 0, 5);
                LANE_IDS();
                if (br) {
                    float* ap = g_acc + ((size_t)(g * 2 + nh) * 12 + warp) * 4096 + ln * 4;
                    acc_store(acc0, ap);
                    acc_store(acc1, ap + 2048);
                } else {
                    const int row = g * 192 + warp * 16 + g8;
                    const bool qp = type == T_QP;
                    WAIT_GRANT();
                    const int ld = qp ? SCR_COLS : 1024;
                    __nv_bfloat16* p = (qp ? g_scr + (((word >> 8) & 7) % RSA) * 512 : P.out) + (size_t)row * ld + nh * 256 + 8 * t4;
                    if (!(P.dbg & 64)) {
                    store_frag(acc0, 1.f, 1.f, p, ld, t4);
                    store_frag(acc1, 1.f, 1.f, p + 128, ld, t4);
                    }
                }
                PROF(threadIdx.x == 0, 2);
                __syncwarp();
                if (lane == 0) mbar_arrive(DONE_BAR);
            } else if (type != T_GQA && !(word & 0x4000) && (word >> 16) != w) {
                SET_SLOT(wrap5(slot + (type == T_FIN ? 4 : 1)));
            } else if (type == T_FIN) {
                const int b = (word >> 4) & 31, q = (word >> 9) & 3;
                float acc[64];
                LANE_IDS();
                WAIT_GRANT();
                {
                    const int tw = (b & 3) * 3 + (wq < 3 ? wq : 0);
                    const float* ap = g_acc + ((size_t)((b >> 2) * 2 + (q >> 1)) * 12 + tw) * 4096 + (q & 1) * 2048 + ln * 4;
#pragma unroll
                    for (int j = 0; j < 16; j++) {
                        const float4 v = __ldcg(reinterpret_cast<const float4*>(ap + j * 128));
                        acc[4 * j] = v.x; acc[4 * j + 1] = v.y; acc[4 * j + 2] = v.z; acc[4 * j + 3] = v.w;
                    }
                }
                mbar_wait_c(bar + 8 * (B_QFULL_PV + w), (st >> 10) & 1);
                st ^= 1u << 10;
                PROF((threadIdx.x & 127) == 0, 1);
                const uint32_t s0 = slot;
                reg_fence(acc);
#pragma unroll 1
                for (int i = 0; i < 4; i++) {
                    mbar_wait_c(bar + 8 * (B_FULL_PV + 5 * w + slot), (st >> (5 + slot)) & 1);
                    st ^= 32u << slot;
                    const uint32_t da = dlo(sb + OFF_Q + i * 12288, 16), db = dlo(ring + slot * SLOT_BYTES, 16384);
                    wg_fence();
#pragma unroll
                    for (int kk = 0; kk < 8; kk++) wgmma_ss_tb<DH128, DH128>(acc, da + (kk >> 2) * 384 + (kk & 3) * 2, db + kk * 128);
                    wg_commit();
                    slot = wrap5(slot + 1);
                }
                wg_wait<0>();
                reg_fence(acc);
                SET_SLOT(slot);
                if (lane == 0) {
                    uint32_t s = s0;
                    for (int i = 0; i < 4; i++) { mbar_arrive_n(bar + 8 * (B_EMPTY + s), 3); s = wrap5(s + 1); }
                    for (int i = 0; i < 3; i++) mbar_arrive(bar + 8 * (B_QEMPTY + i));
                }
                if (wq < 3) {
                    __nv_bfloat16* p = P.out + (size_t)(b * SQ + wq * 16 + g8) * 1024 + 512 + q * 128 + 8 * t4;
                    store_frag(acc, 1.f, 1.f, p, 1024, t4);
                }
                PROF((threadIdx.x & 127) == 0, 2);
                __syncwarp();
                if (lane == 0) mbar_arrive_n(DONE_BAR, 3);
            } else {
                const bool gqa = (type == T_GQA), tri = (word & 0x4000) != 0, all3 = gqa || tri;
                float o[64];
                if (!gqa) {
                    const uint32_t fq = bar + 8 * (tri ? B_FULL_SH : B_FULL_PV + 5 * w), sh = tri ? 0 : 5, cq = tri ? 1 : 3;
#pragma unroll
                    for (int i = 0; i < 64; i++) o[i] = 0.f;
                    uint32_t prev = 0;
#pragma unroll 1
                    for (int i = 0; i < 8; i++) {
                        mbar_wait_c(fq + 8 * slot, (st >> (sh + slot)) & 1);
                        st ^= 1u << (sh + slot);
                        PROF(i == 0 && (threadIdx.x & 127) == 0 && (!tri || w == 0), 1);
                        const uint32_t s = ring + slot * SLOT_BYTES;
                        const uint32_t da = dlo(s + 16384 + (tri ? w * 6144 : 0), 16), db = dlo(s, 8192);
                        wg_fence();
#pragma unroll
                        for (int kk = 0; kk < 4; kk++) wgmma_ss_tb<DH128, DH128>(o, da + kk * 2, db + kk * 128);
                        wg_commit();
                        if (i > 0) {
                            wg_wait<1>();
                            if (lane == 0) mbar_arrive_n(bar + 8 * (B_EMPTY + prev), cq);
                        }
                        prev = slot;
                        slot = wrap5(slot + 1);
                    }
                    wg_wait<0>();
                    reg_fence(o);
                    if (lane == 0) mbar_arrive_n(bar + 8 * (B_EMPTY + prev), cq);
                    mbar_wait_c(bar + 8 * (B_QFULL_PV + w), (st >> 10) & 1);
                    st ^= 1u << 10;
                    LANE_IDS();
                    const uint32_t rowi = wq * 16 + (ln & 15);
                    const uint32_t qa = sb + OFF_Q + w * 8192 + rowi * 128;
#pragma unroll
                    for (int j = 0; j < 16; j += 2) {
                        const uint32_t blk = j + (ln >> 4);
                        const uint32_t a = qa + (j >> 3) * 24576 + (((blk & 7) ^ (ln & 7)) << 4);
                        asm volatile("stmatrix.sync.aligned.m8n8.x4.shared.b16 [%0], {%1, %2, %3, %4};" ::"r"(a),
                                     "r"(pack_bf16(o[4 * j], o[4 * j + 1])), "r"(pack_bf16(o[4 * j + 2], o[4 * j + 3])),
                                     "r"(pack_bf16(o[4 * j + 4], o[4 * j + 5])), "r"(pack_bf16(o[4 * j + 6], o[4 * j + 7])) : "memory");
                    }
                    asm volatile("fence.proxy.async.shared::cta;" ::: "memory");
                    nbar_sync(9 + w, 128);
                    PROF((threadIdx.x & 127) == 0 && (!tri || w == 0), 5);
                } else {
                    mbar_wait_c(bar + 8 * (B_QFULL_PV + w), (st >> 10) & 1);
                    st ^= 1u << 10;
                }
                const uint32_t fb = bar + 8 * (gqa ? B_FULL_SH : B_FULL_PV + 5 * w), sh = gqa ? 0 : 5, cnt = gqa ? 1 : 3;
                if (all3) st ^= 1u << 13;
#define TOK_ME (1 + w + ((st >> 11) & 4))
#define TOK_NEXT (1 + (w == 2 ? 0 : w + 1) + ((st >> 11) & 4))
#pragma unroll
                for (int i = 0; i < 64; i++) o[i] = 0.f;
                float m0 = -INFINITY, m1 = -INFINITY, l0 = 0.f, l1 = 0.f;
                const float cs = 0.08838834764831845f * 1.4426950408889634f;
                const uint32_t dq = dlo(sb + OFF_Q + w * 8192, 16);
                uint32_t ks = tri ? wrap5(slot + w) : slot;
                uint32_t vs = tri ? wrap5(wrap5(slot + 3) + 2 * w) : wrap5(slot + 1);
                SET_SLOT(wrap5(slot + (tri ? 4 : 3)));
                float s[64];
                {
                    const uint32_t dk = __shfl_sync(0xffffffffu, dlo(ring + ks * SLOT_BYTES, 16), 0);
                    mbar_wait_c(fb + 8 * ks, (st >> (sh + ks)) & 1);
                    st ^= 1u << (sh + ks);
                    PROF(gqa && threadIdx.x == 0, 1);
                    if (all3 && w > 0) nbar_sync(TOK_ME, 256);
                    wg_fence();
                    wgmma_ss_first<DH128, DH128>(s, dq, dk);
#pragma unroll
                    for (int kk = 1; kk < 8; kk++) wgmma_ss<DH128, DH128>(s, dq + (kk >> 2) * 1536 + (kk & 3) * 2, dk + (kk >> 2) * 1024 + (kk & 3) * 2);
                    wg_commit();
                    if (all3 && (TOKMODE == 0 || w < 2)) nbar_arrive(TOK_NEXT, 256);
                    wg_wait<0>();
                    reg_fence(s);
                    if (lane == 0) mbar_arrive_n(bar + 8 * (B_EMPTY + ks), cnt);
                }
#pragma unroll 1
                for (int j = 0; j < 4; j++) {
                    TRACE(0);
                    asm volatile("" : "+r"(st));
                    uint32_t pr[32];
                    if (!gqa && wq == 3) {
#pragma unroll
                        for (int i = 0; i < 32; i++) pr[i] = __float_as_uint(s[i]);
                    } else {
                    float xa[4], xb[4];
#pragma unroll
                    for (int i = 0; i < 4; i++) { xa[i] = fmaxf(s[4 * i], s[4 * i + 1]); xb[i] = fmaxf(s[4 * i + 2], s[4 * i + 3]); }
#pragma unroll
                    for (int i = 4; i < 16; i++) {
                        xa[i & 3] = fmaxf(xa[i & 3], fmaxf(s[4 * i], s[4 * i + 1]));
                        xb[i & 3] = fmaxf(xb[i & 3], fmaxf(s[4 * i + 2], s[4 * i + 3]));
                    }
                    float x0 = fmaxf(fmaxf(xa[0], xa[1]), fmaxf(xa[2], xa[3])), x1 = fmaxf(fmaxf(xb[0], xb[1]), fmaxf(xb[2], xb[3]));
                    x0 = fmaxf(x0, __shfl_xor_sync(0xffffffffu, x0, 1));
                    x1 = fmaxf(x1, __shfl_xor_sync(0xffffffffu, x1, 1));
                    x0 = fmaxf(x0, __shfl_xor_sync(0xffffffffu, x0, 2));
                    x1 = fmaxf(x1, __shfl_xor_sync(0xffffffffu, x1, 2));
                    const float n0 = fmaxf(m0, x0), n1 = fmaxf(m1, x1);
                    const float a0 = ex2((m0 - n0) * cs), a1 = ex2((m1 - n1) * cs);
                    m0 = n0; m1 = n1;
                    const float c0 = -n0 * cs, c1 = -n1 * cs;
                    float ra[2] = {l0 * a0, 0.f}, rb[2] = {l1 * a1, 0.f};
#pragma unroll
                    for (int i = 0; i < 16; i++) {
                        const float p0 = ex2(fmaf(s[4 * i], cs, c0)), p1 = ex2(fmaf(s[4 * i + 1], cs, c0));
                        const float p2 = ex2(fmaf(s[4 * i + 2], cs, c1)), p3 = ex2(fmaf(s[4 * i + 3], cs, c1));
                        ra[i & 1] += p0 + p1; rb[i & 1] += p2 + p3;
                        pr[2 * i] = pack_bf16(p0, p1);
                        pr[2 * i + 1] = pack_bf16(p2, p3);
                        o[4 * i] *= a0; o[4 * i + 1] *= a0; o[4 * i + 2] *= a1; o[4 * i + 3] *= a1;
                    }
                    l0 = ra[0] + ra[1]; l1 = rb[0] + rb[1];
                    }
                    ks = wrap5(vs + 1);
                    const uint32_t dv = __shfl_sync(0xffffffffu, dlo(ring + vs * SLOT_BYTES, 16384), 0);
                    const uint32_t dk = __shfl_sync(0xffffffffu, dlo(ring + ks * SLOT_BYTES, 16), 0);
#pragma unroll
                    for (int i = 0; i < 32; i++) asm volatile("" : "+r"(pr[i])::"memory");
                    asm volatile("" : "+f"(l0), "+f"(l1)::"memory");
                    reg_fence(o);
                    TRACE(1);
                    mbar_wait_c(fb + 8 * vs, (st >> (sh + vs)) & 1);
                    st ^= 1u << (sh + vs);
                    TRACE(2);
                    if (TOKMODE == 0 && all3) nbar_sync(TOK_ME, 256);
                    wg_fence();
#pragma unroll
                    for (int kk = 0; kk < 8; kk++) wgmma_rs_tb<DH128>(o, pr[4 * kk], pr[4 * kk + 1], pr[4 * kk + 2], pr[4 * kk + 3], dv + kk * 128);
                    wg_commit();
                    TRACE(3);
                    const uint32_t kbar = fb + 8 * ks, kpar = (st >> (sh + ks)) & 1, vrel = bar + 8 * (B_EMPTY + vs);
                    bool kok = true;
                    if (j < 3) kok = mbar_test(kbar, kpar);
                    else if (TOKMODE == 0 && all3 && w < 2) nbar_arrive(TOK_NEXT, 256);
                    wg_wait<0>();
                    reg_fence(o);
                    if (lane == 0) mbar_arrive_n(vrel, cnt);
                    if (j == 3) break;
                    if (!kok) mbar_wait_c(kbar, kpar);
                    TRACE(5);
                    wg_fence();
                    wgmma_ss_first<DH128, DH128>(s, dq, dk);
#pragma unroll
                    for (int kk = 1; kk < 8; kk++) wgmma_ss<DH128, DH128>(s, dq + (kk >> 2) * 1536 + (kk & 3) * 2, dk + (kk >> 2) * 1024 + (kk & 3) * 2);
                    wg_commit();
                    if (TOKMODE == 0 && all3) nbar_arrive(TOK_NEXT, 256);
                    TRACE(6);
                    st ^= 1u << (sh + ks);
                    wg_wait<0>();
                    reg_fence(s);
                    TRACE(7);
                    if (lane == 0) {
                        mbar_arrive_n(bar + 8 * (B_EMPTY + ks), cnt);
                        if (j == 2) mbar_arrive(bar + 8 * (B_QEMPTY + w));
                    }
                    vs = wrap5(vs + (tri ? ((j == 2 && w > 0) ? 4 * w - 4 : 1) : 2));
                }
                asm volatile("" : "+r"(st));
                WAIT_GRANT();
                if ((gqa || wq < 3) && !(P.dbg & 16)) {
                    LANE_IDS();
                    l0 += __shfl_xor_sync(0xffffffffu, l0, 1);
                    l1 += __shfl_xor_sync(0xffffffffu, l1, 1);
                    l0 += __shfl_xor_sync(0xffffffffu, l0, 2);
                    l1 += __shfl_xor_sync(0xffffffffu, l1, 2);
                    const int b = (word >> 4) & 31;
                    int row, col;
                    if (gqa) { const int hh = warp / 3; row = b * SQ + (warp - hh * 3) * 16; col = (((word >> 9) & 7) % RSA) * 512 + hh * 128; }
                    else { row = (b + (tri ? w : 0)) * SQ + wq * 16; col = SCR_B0 + (((word >> 9) & 31) % RSB) * 128; }
                    store_frag_perm(o, __fdividef(1.f, l0), __fdividef(1.f, l1), g_scr + (size_t)(row + g8) * SCR_COLS + col + 8 * t4, SCR_COLS);
                }
                PROF((threadIdx.x & 127) == 0 && (!all3 || w == 2), 2);
                __syncwarp();
                if (lane == 0) mbar_arrive_n(DONE_BAR, all3 ? 1 : 3);
            }
        }
    }
}

struct Knobs {
    float a0;
    float a1;
    float qlead;
    float owna, ownb;
    float finlag;
    float single;
    float grab, dbg, grid, pkv, pw;
};
Knobs KN = {6.0f, 28.0f, 5.0f, 9.f, 7.f, 3.0f, 26.f, 3.f, 0.f, 0.f, 2.f, 2.f};

typedef CUresult (*EncodeFn)(CUtensorMap*, CUtensorMapDataType, cuuint32_t, void*, const cuuint64_t*, const cuuint64_t*,
                             const cuuint32_t*, const cuuint32_t*, CUtensorMapInterleave, CUtensorMapSwizzle,
                             CUtensorMapL2promotion, CUtensorMapFloatOOBfill);

void enc(EncodeFn fn, CUtensorMap* m, const void* ptr, int rank, uint64_t d0, uint64_t d1, uint64_t d2, uint64_t s1, uint64_t s2,
         uint32_t b0, uint32_t b1, uint32_t b2, CUtensorMapSwizzle sw, bool kv = false) {
    cuuint64_t dims[3] = {d0, d1, d2};
    cuuint64_t strides[2] = {s1, s2};
    cuuint32_t box[3] = {b0, b1, b2};
    cuuint32_t es[3] = {1, 1, 1};
    fn(m, CU_TENSOR_MAP_DATA_TYPE_BFLOAT16, rank, const_cast<void*>(ptr), dims, strides, box, es, CU_TENSOR_MAP_INTERLEAVE_NONE, sw,
       (CUtensorMapL2promotion)(int)(kv ? KN.pkv : KN.pw), CU_TENSOR_MAP_FLOAT_OOB_FILL_NONE);
}

int build_table(uint16_t* table) {
    static float key[NT_MAX];
    static uint16_t word[NT_MAX];
    static int idx[NT_MAX];
    int n = 0;
    for (int h = 0; h < 28; h++)
        for (int b = 0; b < 32;) {
            const bool tri = h + b / 32.f < KN.single && b + 3 <= 32 && !(b == 15);
            key[n] = h + b / 32.f;
            word[n++] = (uint16_t)(T_MHA | 8 | (b << 4) | (h << 9) | (tri ? 0x4000 : 0));
            b += tri ? 3 : 1;
        }
    for (int b = 0; b < 32; b++)
        for (int q = 0; q < 4; q++) {
            key[n] = 28.f + (b * 4 + q) / 32.f;
            word[n++] = (uint16_t)(T_MHA | 8 | (b << 4) | ((28 + q) << 9));
            key[n] = 28.f + (b * 4 + 4 + q) / 32.f + KN.finlag;
            word[n++] = (uint16_t)(T_FIN | 8 | (b << 4) | (q << 9));
        }
    const float da = (KN.a1 - KN.a0) / 256.f;
    for (int r = 0; r < 8; r++)
        for (int g = 0; g < 8; g++) {
            const float ka = KN.a0 + (r * 32 + g * 4) * da;
            for (int i = 0; i < 4; i++) {
                key[n] = ka + i * da + 0.001f;
                word[n++] = (uint16_t)(T_GQA | ((g * 4 + i) << 4) | (r << 9));
            }
            for (int i = 0; i < 2; i++) {
                key[n] = ka - KN.qlead + 2 * i * da;
                word[n++] = (uint16_t)(T_QP | (g << 4) | ((r * 2 + i) << 7));
            }
        }
    for (int i = 0; i < 32; i++) {
        key[n] = (i < 16 ? KN.ownb : KN.owna) + i * 0.001f;
        word[n++] = (uint16_t)(T_OWN | ((1 - (i >> 4)) << 3) | (((i >> 1) & 7) << 4) | ((i & 1) << 7));
    }
    {
        const int dbg = (int)KN.dbg;
        int m = 0;
        for (int i = 0; i < n; i++) {
            const int ty = word[i] & 7;
            if ((ty == T_QP && (dbg & 1)) || (ty == T_GQA && (dbg & 2)) || (ty == T_MHA && (dbg & 4)) || ((ty == T_OWN || ty == T_FIN) && (dbg & 8))) continue;
            key[m] = key[i]; word[m++] = word[i];
        }
        n = m;
    }
    for (int i = 0; i < n; i++) idx[i] = i;
    for (int i = 1; i < n; i++) {
        const int v = idx[i];
        int j = i - 1;
        while (j >= 0 && key[idx[j]] > key[v]) { idx[j + 1] = idx[j]; j--; }
        idx[j + 1] = v;
    }
    for (int i = 0; i < n; i++) table[i] = word[idx[i]];
    for (int i = n; i < NT_MAX; i++) table[i] = T_END;
    return n;
}

}

extern "C" void kernel_launch(void* const* d_in, const int* in_sizes, int n_in, void* d_out, int out_size) {
    (void)in_sizes; (void)n_in; (void)out_size;
    static Params P;
    static int nsm = 0;
    void* fnp = nullptr;
    cudaDriverEntryPointQueryResult qr;
    cudaGetDriverEntryPoint("cuTensorMapEncodeTiled", &fnp, cudaEnableDefault, &qr);
    EncodeFn fn = (EncodeFn)fnp;
    void* scr = nullptr;
    cudaGetSymbolAddress(&scr, g_scr);
    const CUtensorMapSwizzle S128 = CU_TENSOR_MAP_SWIZZLE_128B, S64 = CU_TENSOR_MAP_SWIZZLE_64B;
    enc(fn, &P.maps[M_KA], d_in[1], 3, 64, (uint64_t)NB * 8 * SK, 2, 256, 128, 64, 128, 2, S128, true);
    enc(fn, &P.maps[M_VA], d_in[2], 3, 64, (uint64_t)NB * 8 * SK, 2, 256, 128, 64, 128, 2, S128, true);
    enc(fn, &P.maps[M_KB], d_in[6], 3, 64, (uint64_t)NB * NH * SK, 2, 256, 128, 64, 128, 2, S128, true);
    enc(fn, &P.maps[M_VB], d_in[7], 3, 64, (uint64_t)NB * NH * SK, 2, 256, 128, 64, 128, 2, S128, true);
    enc(fn, &P.maps[M_XA], d_in[0], 2, DM, NTOK, 1, DM * 2, 0, 32, 192, 1, S64);
    enc(fn, &P.maps[M_XB3], d_in[5], 2, DM, NTOK, 1, DM * 2, 0, 64, 144, 1, S128);
    enc(fn, &P.maps[M_XB1], d_in[5], 2, DM, NTOK, 1, DM * 2, 0, 64, 48, 1, S128);
    enc(fn, &P.maps[M_WQA], d_in[3], 3, 64, DM, 64, NH * DH * 2, 128, 64, 32, 4, S128);
    enc(fn, &P.maps[M_WQB], d_in[8], 3, 64, DM, 64, NH * DH * 2, 128, 64, 64, 2, S128);
    for (int i = 0; i < 3; i++) {
        const bool fin = i == 2;
        cuuint64_t dims[5] = {fin ? 512u : 64u, 2, fin ? 4u : 512u, 4, fin ? 128u : 8u};
        cuuint64_t strides[4] = {1024, 8 * 1024, 2 * 1024, fin ? 32u * 1024u : 128u};
        cuuint32_t box[5] = {64, 2, 4, 4, 4}, es[5] = {1, 1, 1, 1, 1};
        fn(&P.maps[M_WOA + i], CU_TENSOR_MAP_DATA_TYPE_BFLOAT16, 5, d_in[i ? 9 : 4], dims, strides, box, es, CU_TENSOR_MAP_INTERLEAVE_NONE, S128,
           (CUtensorMapL2promotion)(int)KN.pw, CU_TENSOR_MAP_FLOAT_OOB_FILL_NONE);
    }
    enc(fn, &P.maps[M_SA], scr, 2, SCR_COLS, NTOK, 1, SCR_COLS * 2, 0, 32, 192, 1, S64);
    enc(fn, &P.maps[M_SQ], scr, 2, SCR_COLS, NTOK, 1, SCR_COLS * 2, 0, 64, 48, 1, S128);
    enc(fn, &P.maps[M_SQ16], scr, 2, SCR_COLS, NTOK, 1, SCR_COLS * 2, 0, 64, 16, 1, S128);
    P.out = (__nv_bfloat16*)d_out;
    P.nt = (uint32_t)build_table(P.table);
    P.grab = (int)KN.grab; P.dbg = (int)KN.dbg;
    if (nsm == 0) {
        int dev = 0;
        cudaGetDevice(&dev);
        cudaDeviceGetAttribute(&nsm, cudaDevAttrMultiProcessorCount, dev);
        cudaFuncSetAttribute(fused_attn_kernel, cudaFuncAttributeMaxDynamicSharedMemorySize, SMEM_BYTES);
    }
    fused_attn_kernel<<<KN.grid > 0 ? (int)KN.grid : nsm, 512, SMEM_BYTES>>>(P);
}
```

```cpp
#include <cuda_runtime.h>
#include <cuda_bf16.h>
#include <cuda.h>
#include <stdint.h>

#define K_RSA 2
#define K_RSB 7
#define EXPM 1
#define K_HQ 32

namespace {

constexpr int NB = 32, SQ = 48, DM = 512, NH = 32, SK = 512, DH = 128;
constexpr int NTOK = NB * SQ;
constexpr int RSA = K_RSA;
constexpr int RSB = K_RSB;
constexpr int SCR_B0 = RSA * 16;
constexpr int SCR_BLKS = SCR_B0 + RSB * 4;
constexpr int SCR_BATCH = SCR_BLKS * SQ * 32;
constexpr int HQ = K_HQ;
constexpr int NSLOT = 5;
constexpr int SLOT_BYTES = 35840;
constexpr int QBUF_BYTES = 49152;
constexpr int NT_MAX = 1200;

enum : uint32_t { T_QP = 0, T_MHA = 1, T_GQA = 2, T_OWN = 3, T_FIN = 4, T_END = 5 };

enum { M_KA, M_VA, M_KB, M_VB, M_XA, M_XB3, M_XB1, M_WQA, M_WQB, M_WOA, M_WOB, M_WOF, M_SA, M_SQ, M_WQP, M_XP, M_Q, M_COUNT };

struct Params {
    CUtensorMap maps[M_COUNT];
    __nv_bfloat16* out;
    uint32_t nt;
    int grab, bq;
    uint32_t capt, caps, capq, capg;
    int dbg;
    uint16_t table[NT_MAX];
};

constexpr int F_QF = 0;
constexpr int F_OFA = 64;
constexpr int F_RFA = 128;
constexpr int F_OFB = 192;
constexpr int F_RFB = 448;
constexpr int F_AF = 704;
constexpr int F_FB = 720;
constexpr int F_COUNT = 752;

__device__ __align__(1024) __nv_bfloat16 g_scr[NB * SCR_BATCH];
__device__ __align__(1024) __nv_bfloat16 g_q[NB * (NH - HQ) * SQ * DH + 8192];
__device__ __align__(128) unsigned int g_flags[F_COUNT * 8];
__device__ __align__(128) unsigned int g_task_ctr[32];
__device__ __align__(128) unsigned long long g_ticket[16];
#define PROF(cond, k) do {} while (0)
#define TRACE(k) do {} while (0)

constexpr int OFF_Q = 0;
constexpr int OFF_RING = QBUF_BYTES;
constexpr int OFF_BAR = OFF_RING + NSLOT * SLOT_BYTES;
constexpr int B_FULL_SH = 0;
constexpr int B_FULL_PV = 5;
constexpr int B_EMPTY = 20;
constexpr int B_QFULL_PV = 25;
constexpr int B_QEMPTY = 29;
constexpr int B_GRANT = 32;
constexpr int B_MBFULL = 36;
constexpr int B_MBEMPTY = 40;
constexpr int B_DONE = 44;
constexpr int B_SETUP = 48;
constexpr int B_WANT = 49;
constexpr int B_FINA = 50;
constexpr int B_LAST = 53;
constexpr int OFF_MBOX = OFF_BAR + 512;
constexpr int OFF_TABLE = OFF_MBOX + 64;
constexpr int SMEM_BYTES = OFF_TABLE + NT_MAX * 2 + 1024;

constexpr uint32_t DH128 = (1024u >> 4) | (1u << 30);
constexpr uint32_t DH64 = (512u >> 4) | (2u << 30);
constexpr uint32_t DHKV = (2048u >> 4) | (1u << 30);

__device__ __forceinline__ uint32_t smem_u32(const void* p) { return (uint32_t)__cvta_generic_to_shared(p); }
__device__ __forceinline__ void mbar_init(uint32_t a, uint32_t c) { asm volatile("mbarrier.init.shared::cta.b64 [%0], %1;" ::"r"(a), "r"(c)); }
__device__ __forceinline__ void mbar_expect(uint32_t a, uint32_t bytes) { asm volatile("mbarrier.arrive.expect_tx.shared::cta.b64 _, [%0], %1;" ::"r"(a), "r"(bytes) : "memory"); }
__device__ __forceinline__ void mbar_arrive(uint32_t a) { asm volatile("mbarrier.arrive.shared::cta.b64 _, [%0];" ::"r"(a) : "memory"); }
__device__ __forceinline__ void mbar_arrive_n(uint32_t a, uint32_t n) { asm volatile("mbarrier.arrive.shared::cta.b64 _, [%0], %1;" ::"r"(a), "r"(n) : "memory"); }
__device__ __forceinline__ bool mbar_try(uint32_t a, uint32_t parity) {
    uint32_t ok;
    asm volatile("{\n.reg .pred p;\nmbarrier.try_wait.parity.shared::cta.b64 p, [%1], %2;\nselp.u32 %0, 1, 0, p;\n}\n" : "=r"(ok) : "r"(a), "r"(parity) : "memory");
    return ok != 0;
}
__device__ __forceinline__ bool mbar_test(uint32_t a, uint32_t parity) {
    uint32_t ok;
    asm volatile("{\n.reg .pred p;\nmbarrier.test_wait.parity.shared::cta.b64 p, [%1], %2;\nselp.u32 %0, 1, 0, p;\n}\n" : "=r"(ok) : "r"(a), "r"(parity) : "memory");
    return ok != 0;
}
__device__ __forceinline__ void mbar_wait(uint32_t a, uint32_t parity) {
    uint32_t n = 0;
    while (!mbar_try(a, parity)) { if (++n > (1u << 22)) __trap(); }
}
__device__ __forceinline__ void mbar_wait_c(uint32_t a, uint32_t parity) {
    while (!mbar_try(a, parity)) {}
}
__device__ __forceinline__ void tma2d(uint32_t dst, const CUtensorMap* m, int c0, int c1, uint32_t bar) {
    asm volatile("cp.async.bulk.tensor.2d.shared::cluster.global.mbarrier::complete_tx::bytes [%0], [%1, {%3, %4}], [%2];"
                 ::"r"(dst), "l"(m), "r"(bar), "r"(c0), "r"(c1) : "memory");
}
__device__ __forceinline__ void tma3d(uint32_t dst, const CUtensorMap* m, int c1, int c2, uint32_t bar) {
    asm volatile("cp.async.bulk.tensor.3d.shared::cluster.global.mbarrier::complete_tx::bytes [%0], [%1, {%3, %4, %5}], [%2];"
                 ::"r"(dst), "l"(m), "r"(bar), "r"(0), "r"(c1), "r"(c2) : "memory");
}
__device__ __forceinline__ void tma3d_h(uint32_t dst, const CUtensorMap* m, int c1, int c2, uint32_t bar, uint64_t pol) {
    asm volatile("cp.async.bulk.tensor.3d.shared::cluster.global.mbarrier::complete_tx::bytes.L2::cache_hint [%0], [%1, {%3, %4, %5}], [%2], %6;"
                 ::"r"(dst), "l"(m), "r"(bar), "r"(0), "r"(c1), "r"(c2), "l"(pol) : "memory");
}
__device__ __forceinline__ void tma5d_h(uint32_t dst, const CUtensorMap* m, int c0, int c2, int c4, uint32_t bar, uint64_t pol) {
    asm volatile("cp.async.bulk.tensor.5d.shared::cluster.global.mbarrier::complete_tx::bytes.L2::cache_hint [%0], [%1, {%4, %3, %5, %3, %6}], [%2], %7;"
                 ::"r"(dst), "l"(m), "r"(bar), "r"(0), "r"(c0), "r"(c2), "r"(c4), "l"(pol) : "memory");
}
__device__ __forceinline__ void tma5d(uint32_t dst, const CUtensorMap* m, int c0, int c2, int c4, uint32_t bar) {
    asm volatile("cp.async.bulk.tensor.5d.shared::cluster.global.mbarrier::complete_tx::bytes [%0], [%1, {%4, %3, %5, %3, %6}], [%2];"
                 ::"r"(dst), "l"(m), "r"(bar), "r"(0), "r"(c0), "r"(c2), "r"(c4) : "memory");
}
__device__ __forceinline__ void tma_stream(uint32_t dst, const CUtensorMap* m, int c1, uint32_t bar, uint64_t pol) {
    asm volatile("cp.async.bulk.tensor.4d.shared::cluster.global.mbarrier::complete_tx::bytes.L2::cache_hint [%0], [%1, {%3, %3, %3, %4}], [%2], %5;"
                 ::"r"(dst), "l"(m), "r"(bar), "r"(0), "r"(c1), "l"(pol) : "memory");
}
__device__ __forceinline__ bool elect_one() {
    uint32_t p;
    asm volatile("{\n.reg .pred p;\nelect.sync _|p, 0xffffffff;\nselp.u32 %0, 1, 0, p;\n}\n" : "=r"(p));
    return p != 0;
}
__device__ __forceinline__ int lane_id() { int l; asm volatile("mov.u32 %0, %%laneid;" : "=r"(l)); return l; }
__device__ __forceinline__ uint32_t tri_pos(int i) {
    if (i < 3) return i << 3;
    if (i >= 21) return ((i - 21) << 3) | 7;
    const int v = i - 3, j = (v * 43) >> 8, c = v - 6 * j;
    return ((c >> 1) << 3) | (2 * j + 1 + (c & 1));
}
__device__ __forceinline__ void fence_proxy_async_global() { asm volatile("fence.proxy.async.global;" ::: "memory"); }
__device__ __forceinline__ void poll_flag(int idx, uint32_t target) {
    const unsigned int* p = &g_flags[idx * 8];
    uint32_t n = 0;
    while (true) {
        uint32_t v;
        asm volatile("ld.relaxed.gpu.global.u32 %0, [%1];" : "=r"(v) : "l"(p) : "memory");
        if ((int32_t)(v - target) >= 0) break;
        if (++n > (1u << 21)) __trap();
        __nanosleep(64);
    }
    asm volatile("fence.acquire.gpu;" ::: "memory");
}
__device__ __forceinline__ void flag_add(int idx, int sub = 0) {
    asm volatile("red.relaxed.gpu.global.add.u32 [%0], 1;" ::"l"(&g_flags[idx * 8 + sub]) : "memory");
}
__device__ __forceinline__ void wg_fence() { asm volatile("wgmma.fence.sync.aligned;" ::: "memory"); }
__device__ __forceinline__ void wg_commit() { asm volatile("wgmma.commit_group.sync.aligned;" ::: "memory"); }
template <int N> __device__ __forceinline__ void wg_wait() { asm volatile("wgmma.wait_group.sync.aligned %0;" ::"n"(N) : "memory"); }
template <int N> __device__ __forceinline__ void reg_fence(float (&d)[N]) {
#pragma unroll
    for (int i = 0; i < N; i++) asm volatile("" : "+f"(d[i])::"memory");
}
__device__ __forceinline__ void nbar_sync(uint32_t id, uint32_t n) { asm volatile("barrier.cta.sync %0, %1;" ::"r"(id), "r"(n) : "memory"); }
__device__ __forceinline__ void nbar_arrive(uint32_t id, uint32_t n) { asm volatile("barrier.cta.arrive %0, %1;" ::"r"(id), "r"(n) : "memory"); }
__device__ __forceinline__ uint32_t dlo(uint32_t addr, uint32_t lbo) { return (addr >> 4) | ((lbo >> 4) << 16); }
__device__ __forceinline__ uint32_t pack_bf16(float lo, float hi) {
    uint32_t r;
    asm("cvt.rn.bf16x2.f32 %0, %1, %2;" : "=r"(r) : "f"(hi), "f"(lo));
    return r;
}
__device__ __forceinline__ float ex2(float x) { float y; asm("ex2.approx.ftz.f32 %0, %1;" : "=f"(y) : "f"(x)); return y; }
__device__ __forceinline__ uint32_t wrap3(uint32_t s) { return s >= 3 ? s - 3 : s; }
__device__ __forceinline__ uint32_t wrap5(uint32_t s) { return s >= NSLOT ? s - NSLOT : s; }
__device__ __forceinline__ uint4 quad_transpose(uint32_t v0, uint32_t v1, uint32_t v2, uint32_t v3, int t) {
    const bool o1 = t & 1, o2 = t & 2;
    uint32_t s0 = __shfl_xor_sync(0xffffffffu, o1 ? v0 : v1, 1);
    uint32_t s1 = __shfl_xor_sync(0xffffffffu, o1 ? v2 : v3, 1);
    uint32_t a0 = o1 ? s0 : v0, a1 = o1 ? v1 : s0, b0 = o1 ? s1 : v2, b1 = o1 ? v3 : s1;
    uint32_t r0 = __shfl_xor_sync(0xffffffffu, o2 ? a0 : b0, 2);
    uint32_t r1 = __shfl_xor_sync(0xffffffffu, o2 ? a1 : b1, 2);
    uint4 o;
    o.x = o2 ? r0 : a0; o.y = o2 ? r1 : a1; o.z = o2 ? b0 : r0; o.w = o2 ? b1 : r1;
    return o;
}
__device__ __forceinline__ void store_frag(const float (&d)[64], __nv_bfloat16* p, int ld, int js, int t) {
#pragma unroll
    for (int j = 0; j < 16; j += 4) {
        uint4 lo = quad_transpose(pack_bf16(d[4 * j], d[4 * j + 1]), pack_bf16(d[4 * j + 4], d[4 * j + 5]),
                                  pack_bf16(d[4 * j + 8], d[4 * j + 9]), pack_bf16(d[4 * j + 12], d[4 * j + 13]), t);
        uint4 hi = quad_transpose(pack_bf16(d[4 * j + 2], d[4 * j + 3]), pack_bf16(d[4 * j + 6], d[4 * j + 7]),
                                  pack_bf16(d[4 * j + 10], d[4 * j + 11]), pack_bf16(d[4 * j + 14], d[4 * j + 15]), t);
        *reinterpret_cast<uint4*>(p + (j & 4) * 8 + (j >> 3) * js) = lo;
        *reinterpret_cast<uint4*>(p + (j & 4) * 8 + (j >> 3) * js + 8 * ld) = hi;
    }
}
__device__ __forceinline__ void store_q(const float (&d)[64], uint32_t qa, int ln) {
#pragma unroll
    for (int j = 0; j < 16; j += 2) {
        const uint32_t a = qa + (j >> 3) * 24576 + ((((j + (ln >> 4)) & 7) ^ (ln & 7)) << 4);
        asm volatile("stmatrix.sync.aligned.m8n8.x4.shared.b16 [%0], {%1, %2, %3, %4};" ::"r"(a), "r"(pack_bf16(d[4 * j], d[4 * j + 1])),
                     "r"(pack_bf16(d[4 * j + 2], d[4 * j + 3])), "r"(pack_bf16(d[4 * j + 4], d[4 * j + 5])), "r"(pack_bf16(d[4 * j + 6], d[4 * j + 7])) : "memory");
    }
}
__device__ __forceinline__ void st16(__nv_bfloat16* p, uint32_t a, uint32_t b, uint32_t c, uint32_t d) {
    if (EXPM & 4) {
        uint64_t pol;
        asm("createpolicy.fractional.L2::evict_first.b64 %0, 1.0;" : "=l"(pol));
        asm volatile("st.global.L2::cache_hint.v4.u32 [%0], {%1, %2, %3, %4}, %5;" ::"l"(p), "r"(a), "r"(b), "r"(c), "r"(d), "l"(pol) : "memory");
    } else *reinterpret_cast<uint4*>(p) = make_uint4(a, b, c, d);
}
__device__ __forceinline__ void store_frag_perm(const float (&d)[64], float s0, float s1, __nv_bfloat16* p) {
#pragma unroll
    for (int j = 0; j < 16; j += 4) {
        st16(p + (j >> 2) * (SQ * 32), pack_bf16(d[4 * j] * s0, d[4 * j + 1] * s0), pack_bf16(d[4 * j + 4] * s0, d[4 * j + 5] * s0),
             pack_bf16(d[4 * j + 8] * s0, d[4 * j + 9] * s0), pack_bf16(d[4 * j + 12] * s0, d[4 * j + 13] * s0));
        st16(p + (j >> 2) * (SQ * 32) + 256, pack_bf16(d[4 * j + 2] * s1, d[4 * j + 3] * s1), pack_bf16(d[4 * j + 6] * s1, d[4 * j + 7] * s1),
             pack_bf16(d[4 * j + 10] * s1, d[4 * j + 11] * s1), pack_bf16(d[4 * j + 14] * s1, d[4 * j + 15] * s1));
    }
}
__device__ __forceinline__ uint4* acc_ptr(int b, int rb, int nh) {
    return reinterpret_cast<uint4*>(g_scr + (size_t)b * SCR_BATCH + (6 % RSA) * 16 * SQ * 32) + (rb * 2 + nh) * 512;
}
__device__ __forceinline__ void acc_store(const float (&d)[64], uint4* ap) {
#pragma unroll
    for (int j = 0; j < 8; j++)
        ap[j * 32] = make_uint4(pack_bf16(d[8 * j], d[8 * j + 1]), pack_bf16(d[8 * j + 2], d[8 * j + 3]), pack_bf16(d[8 * j + 4], d[8 * j + 5]),
                                pack_bf16(d[8 * j + 6], d[8 * j + 7]));
}

template <uint32_t AH, uint32_t BH>
__device__ __forceinline__ void wgmma_ss(float (&d)[64], uint32_t da, uint32_t db) {
    asm volatile("{\n.reg .pred p;\n.reg .b64 a, b;\n.reg .b32 x, y;\nsetp.eq.b32 p, 0, 0;\nmov.b32 x, %66;\nmov.b32 y, %67;\nmov.b64 a, {%64, x};\nmov.b64 b, {%65, y};\n"
        "wgmma.mma_async.sync.aligned.m64n128k16.f32.bf16.bf16 "
        "{%0, %1, %2, %3, %4, %5, %6, %7, %8, %9, %10, %11, %12, %13, %14, %15, %16, %17, %18, %19, %20, %21, %22, %23, "
        "%24, %25, %26, %27, %28, %29, %30, %31, %32, %33, %34, %35, %36, %37, %38, %39, %40, %41, %42, %43, %44, %45, "
        "%46, %47, %48, %49, %50, %51, %52, %53, %54, %55, %56, %57, %58, %59, %60, %61, %62, %63}, "
        "a, b, p, 1, 1, 0, 0;\n}\n"
        : "+f"(d[0]), "+f"(d[1]), "+f"(d[2]), "+f"(d[3]), "+f"(d[4]), "+f"(d[5]), "+f"(d[6]), "+f"(d[7]), "+f"(d[8]),
          "+f"(d[9]), "+f"(d[10]), "+f"(d[11]), "+f"(d[12]), "+f"(d[13]), "+f"(d[14]), "+f"(d[15]), "+f"(d[16]),
          "+f"(d[17]), "+f"(d[18]), "+f"(d[19]), "+f"(d[20]), "+f"(d[21]), "+f"(d[22]), "+f"(d[23]), "+f"(d[24]),
          "+f"(d[25]), "+f"(d[26]), "+f"(d[27]), "+f"(d[28]), "+f"(d[29]), "+f"(d[30]), "+f"(d[31]), "+f"(d[32]),
          "+f"(d[33]), "+f"(d[34]), "+f"(d[35]), "+f"(d[36]), "+f"(d[37]), "+f"(d[38]), "+f"(d[39]), "+f"(d[40]),
          "+f"(d[41]), "+f"(d[42]), "+f"(d[43]), "+f"(d[44]), "+f"(d[45]), "+f"(d[46]), "+f"(d[47]), "+f"(d[48]),
          "+f"(d[49]), "+f"(d[50]), "+f"(d[51]), "+f"(d[52]), "+f"(d[53]), "+f"(d[54]), "+f"(d[55]), "+f"(d[56]),
          "+f"(d[57]), "+f"(d[58]), "+f"(d[59]), "+f"(d[60]), "+f"(d[61]), "+f"(d[62]), "+f"(d[63])
        : "r"(da), "r"(db), "n"(AH), "n"(BH));
}

template <uint32_t AH, uint32_t BH>
__device__ __forceinline__ void wgmma_ss_first(float (&d)[64], uint32_t da, uint32_t db) {
    asm volatile("{\n.reg .pred p;\n.reg .b64 a, b;\n.reg .b32 x, y;\nsetp.ne.b32 p, 0, 0;\nmov.b32 x, %66;\nmov.b32 y, %67;\nmov.b64 a, {%64, x};\nmov.b64 b, {%65, y};\n"
        "wgmma.mma_async.sync.aligned.m64n128k16.f32.bf16.bf16 "
        "{%0, %1, %2, %3, %4, %5, %6, %7, %8, %9, %10, %11, %12, %13, %14, %15, %16, %17, %18, %19, %20, %21, %22, %23, "
        "%24, %25, %26, %27, %28, %29, %30, %31, %32, %33, %34, %35, %36, %37, %38, %39, %40, %41, %42, %43, %44, %45, "
        "%46, %47, %48, %49, %50, %51, %52, %53, %54, %55, %56, %57, %58, %59, %60, %61, %62, %63}, "
        "a, b, p, 1, 1, 0, 0;\n}\n"
        : "=f"(d[0]), "=f"(d[1]), "=f"(d[2]), "=f"(d[3]), "=f"(d[4]), "=f"(d[5]), "=f"(d[6]), "=f"(d[7]), "=f"(d[8]),
          "=f"(d[9]), "=f"(d[10]), "=f"(d[11]), "=f"(d[12]), "=f"(d[13]), "=f"(d[14]), "=f"(d[15]), "=f"(d[16]),
          "=f"(d[17]), "=f"(d[18]), "=f"(d[19]), "=f"(d[20]), "=f"(d[21]), "=f"(d[22]), "=f"(d[23]), "=f"(d[24]),
          "=f"(d[25]), "=f"(d[26]), "=f"(d[27]), "=f"(d[28]), "=f"(d[29]), "=f"(d[30]), "=f"(d[31]), "=f"(d[32]),
          "=f"(d[33]), "=f"(d[34]), "=f"(d[35]), "=f"(d[36]), "=f"(d[37]), "=f"(d[38]), "=f"(d[39]), "=f"(d[40]),
          "=f"(d[41]), "=f"(d[42]), "=f"(d[43]), "=f"(d[44]), "=f"(d[45]), "=f"(d[46]), "=f"(d[47]), "=f"(d[48]),
          "=f"(d[49]), "=f"(d[50]), "=f"(d[51]), "=f"(d[52]), "=f"(d[53]), "=f"(d[54]), "=f"(d[55]), "=f"(d[56]),
          "=f"(d[57]), "=f"(d[58]), "=f"(d[59]), "=f"(d[60]), "=f"(d[61]), "=f"(d[62]), "=f"(d[63])
        : "r"(da), "r"(db), "n"(AH), "n"(BH));
}

template <uint32_t AH, uint32_t BH>
__device__ __forceinline__ void wgmma_ss_tb(float (&d)[64], uint32_t da, uint32_t db) {
    asm volatile("{\n.reg .pred p;\n.reg .b64 a, b;\n.reg .b32 x, y;\nsetp.eq.b32 p, 0, 0;\nmov.b32 x, %66;\nmov.b32 y, %67;\nmov.b64 a, {%64, x};\nmov.b64 b, {%65, y};\n"
        "wgmma.mma_async.sync.aligned.m64n128k16.f32.bf16.bf16 "
        "{%0, %1, %2, %3, %4, %5, %6, %7, %8, %9, %10, %11, %12, %13, %14, %15, %16, %17, %18, %19, %20, %21, %22, %23, "
        "%24, %25, %26, %27, %28, %29, %30, %31, %32, %33, %34, %35, %36, %37, %38, %39, %40, %41, %42, %43, %44, %45, "
        "%46, %47, %48, %49, %50, %51, %52, %53, %54, %55, %56, %57, %58, %59, %60, %61, %62, %63}, "
        "a, b, p, 1, 1, 0, 1;\n}\n"
        : "+f"(d[0]), "+f"(d[1]), "+f"(d[2]), "+f"(d[3]), "+f"(d[4]), "+f"(d[5]), "+f"(d[6]), "+f"(d[7]), "+f"(d[8]),
          "+f"(d[9]), "+f"(d[10]), "+f"(d[11]), "+f"(d[12]), "+f"(d[13]), "+f"(d[14]), "+f"(d[15]), "+f"(d[16]),
          "+f"(d[17]), "+f"(d[18]), "+f"(d[19]), "+f"(d[20]), "+f"(d[21]), "+f"(d[22]), "+f"(d[23]), "+f"(d[24]),
          "+f"(d[25]), "+f"(d[26]), "+f"(d[27]), "+f"(d[28]), "+f"(d[29]), "+f"(d[30]), "+f"(d[31]), "+f"(d[32]),
          "+f"(d[33]), "+f"(d[34]), "+f"(d[35]), "+f"(d[36]), "+f"(d[37]), "+f"(d[38]), "+f"(d[39]), "+f"(d[40]),
          "+f"(d[41]), "+f"(d[42]), "+f"(d[43]), "+f"(d[44]), "+f"(d[45]), "+f"(d[46]), "+f"(d[47]), "+f"(d[48]),
          "+f"(d[49]), "+f"(d[50]), "+f"(d[51]), "+f"(d[52]), "+f"(d[53]), "+f"(d[54]), "+f"(d[55]), "+f"(d[56]),
          "+f"(d[57]), "+f"(d[58]), "+f"(d[59]), "+f"(d[60]), "+f"(d[61]), "+f"(d[62]), "+f"(d[63])
        : "r"(da), "r"(db), "n"(AH), "n"(BH));
}

template <uint32_t BH>
__device__ __forceinline__ void wgmma_rs_tb(float (&d)[64], uint32_t a0, uint32_t a1, uint32_t a2, uint32_t a3, uint32_t db) {
    asm volatile("{\n.reg .pred p;\n.reg .b64 b;\n.reg .b32 y;\nsetp.eq.b32 p, 0, 0;\nmov.b32 y, %69;\nmov.b64 b, {%68, y};\n"
        "wgmma.mma_async.sync.aligned.m64n128k16.f32.bf16.bf16 "
        "{%0, %1, %2, %3, %4, %5, %6, %7, %8, %9, %10, %11, %12, %13, %14, %15, %16, %17, %18, %19, %20, %21, %22, %23, "
        "%24, %25, %26, %27, %28, %29, %30, %31, %32, %33, %34, %35, %36, %37, %38, %39, %40, %41, %42, %43, %44, %45, "
        "%46, %47, %48, %49, %50, %51, %52, %53, %54, %55, %56, %57, %58, %59, %60, %61, %62, %63}, "
        "{%64, %65, %66, %67}, b, p, 1, 1, 1;\n}\n"
        : "+f"(d[0]), "+f"(d[1]), "+f"(d[2]), "+f"(d[3]), "+f"(d[4]), "+f"(d[5]), "+f"(d[6]), "+f"(d[7]), "+f"(d[8]),
          "+f"(d[9]), "+f"(d[10]), "+f"(d[11]), "+f"(d[12]), "+f"(d[13]), "+f"(d[14]), "+f"(d[15]), "+f"(d[16]),
          "+f"(d[17]), "+f"(d[18]), "+f"(d[19]), "+f"(d[20]), "+f"(d[21]), "+f"(d[22]), "+f"(d[23]), "+f"(d[24]),
          "+f"(d[25]), "+f"(d[26]), "+f"(d[27]), "+f"(d[28]), "+f"(d[29]), "+f"(d[30]), "+f"(d[31]), "+f"(d[32]),
          "+f"(d[33]), "+f"(d[34]), "+f"(d[35]), "+f"(d[36]), "+f"(d[37]), "+f"(d[38]), "+f"(d[39]), "+f"(d[40]),
          "+f"(d[41]), "+f"(d[42]), "+f"(d[43]), "+f"(d[44]), "+f"(d[45]), "+f"(d[46]), "+f"(d[47]), "+f"(d[48]),
          "+f"(d[49]), "+f"(d[50]), "+f"(d[51]), "+f"(d[52]), "+f"(d[53]), "+f"(d[54]), "+f"(d[55]), "+f"(d[56]),
          "+f"(d[57]), "+f"(d[58]), "+f"(d[59]), "+f"(d[60]), "+f"(d[61]), "+f"(d[62]), "+f"(d[63])
        : "r"(a0), "r"(a1), "r"(a2), "r"(a3), "r"(db), "n"(BH));
}

__global__ void __launch_bounds__(512, 1) fused_attn_kernel(const __grid_constant__ Params P) {
    extern __shared__ uint8_t smem_raw[];
    const uint32_t sb = (smem_u32(smem_raw) + 1023u) & ~1023u;
    uint8_t* sgen = smem_raw + (sb - smem_u32(smem_raw));
    const uint32_t bar = sb + OFF_BAR;
    volatile uint32_t* mbox = reinterpret_cast<volatile uint32_t*>(sgen + OFF_MBOX);
    const int warp = __shfl_sync(0xffffffffu, threadIdx.x >> 5, 0), lane = threadIdx.x & 31;

    if (lane == 0) {
#pragma unroll 1
        for (int i = warp; i <= B_LAST; i += 16)
            mbar_init(bar + 8 * i, ((i >= B_EMPTY && i < B_QFULL_PV) || (i >= B_DONE && i < B_SETUP)) ? 12 : (i >= B_QEMPTY && i < B_GRANT) ? 4
                                   : (i >= B_MBEMPTY && i < B_DONE) ? 15 : 1);
        if (warp == B_MBFULL - 32) { mbox[0] = P.table[blockIdx.x]; mbox[4] = blockIdx.x; mbox[9] = 0; mbar_arrive(bar + 8 * B_MBFULL); }
        asm volatile("fence.mbarrier_init.release.cluster;" ::: "memory");
        asm volatile("fence.proxy.async.shared::cta;" ::: "memory");
    }
    __syncwarp();
    nbar_arrive(warp == 15 ? 0 : 13, 512);

    if (warp < 12) {
        asm volatile("setmaxnreg.inc.sync.aligned.u32 160;");
        nbar_sync(0, 512);
        const uint32_t w = warp >> 2, wq = warp & 3;
        uint32_t st = 0;
        const uint32_t ring = sb + OFF_RING;
#define MB_ADDR(base) (bar + 8 * (base) + ((st >> 13) & 24))
#define MB_PAR ((st >> 18) & 1)
#define DONE_BAR MB_ADDR(B_DONE)
#define WAIT_GRANT() mbar_wait_c(MB_ADDR(B_GRANT), MB_PAR)
#define SET_SLOT(x) st = (st & ~(7u << 20)) | ((x) << 20)
        for (;; st = (st & ~(7u << 16)) | ((st + (1u << 16)) & (7u << 16))) {
            asm volatile("" : "+r"(st));
            mbar_wait_c(MB_ADDR(B_MBFULL), MB_PAR);
            const uint32_t word = __shfl_sync(0xffffffffu, mbox[(st >> 16) & 3], 0);
            if (lane == 0) mbar_arrive(MB_ADDR(B_MBEMPTY));
            uint32_t slot = st >> 20;
            const uint32_t type = word & 7;
            if (type == T_END) break;
#define LANE_IDS() const int ln = lane_id(); const int g8 = ln >> 2, t4 = ln & 3; (void)g8; (void)t4

            if (type == T_OWN || type == T_QP) {
                float acc0[64], acc1[64];
#pragma unroll
                for (int i = 0; i < 64; i++) { acc0[i] = 0.f; acc1[i] = 0.f; }
                const uint32_t br = (word >> 3) & 1, g = (word >> 4) & 7, nh = (word >> 7) & 1;
                const int n = type == T_QP ? 16 : br ? 112 : 128;
                const uint32_t bmask = type == T_QP ? 255 : br ? 3 : 15;
#pragma unroll 1
                for (int i = 0; i < n; i++) {
                    mbar_wait_c(bar + 8 * (B_FULL_SH + slot), (st >> slot) & 1);
                    st ^= 1u << slot;
                    PROF(i == 0 && threadIdx.x == 0, 1);
                    const uint32_t s = ring + slot * SLOT_BYTES;
                    const uint32_t da = dlo(s + 16384 + w * 4096, 16), db = dlo(s, 4096);
                    wg_fence();
                    wgmma_ss_tb<DH64, DH128>(acc0, da, db);
                    wgmma_ss_tb<DH64, DH128>(acc1, da, db + 512);
                    wgmma_ss_tb<DH64, DH128>(acc0, da + 2, db + 128);
                    wgmma_ss_tb<DH64, DH128>(acc1, da + 2, db + 640);
                    wg_commit();
                    if ((i & bmask) == bmask && threadIdx.x == 0) flag_add((br ? F_RFB + (i >> 2) * 8 : F_RFA + (i >> 4) * 8) + g);
                    wg_wait<0>();
                    if (lane == 0) mbar_arrive(bar + 8 * (B_EMPTY + slot));
                    slot = wrap5(slot + 1);
                }
                reg_fence(acc0);
                reg_fence(acc1);
                SET_SLOT(slot);
                asm volatile("" : "+r"(st));
                PROF(threadIdx.x == 0, 5);
                LANE_IDS();
                if (br) {
                    WAIT_GRANT();
                    uint4* ap = acc_ptr(g * 4 + warp / 3, warp % 3, nh) + ln;
                    acc_store(acc0, ap);
                    acc_store(acc1, ap + 256);
                } else {
                    const bool qp = type == T_QP;
                    const int bb = warp / 3, ld = qp ? 64 : 1024, js = qp ? SQ * 64 : 64;
                    __nv_bfloat16* p = qp ? g_q + (size_t)((g * 4 + bb) * (NH - HQ) + ((word >> 7) & 15) * 2 - HQ) * (SQ * DH) + ((warp - bb * 3) * 16 + g8) * 64 + 8 * t4
                                          : P.out + (size_t)(g * 192 + warp * 16 + g8) * 1024 + nh * 256 + 8 * t4;
                    store_frag(acc0, p, ld, js, t4);
                    store_frag(acc1, p + 2 * js, ld, js, t4);
                }
                PROF(threadIdx.x == 0, 2);
                __syncwarp();
                if (lane == 0) mbar_arrive(DONE_BAR);
            } else if (type == T_FIN ? (word >> 16) != w : (type == T_MHA && !(word & 0x4000) && wrap3((word >> 16) + 2) == w)) {
                SET_SLOT(wrap5(slot + (type == T_FIN ? 4 : (word & 0x8000) ? 3 : 1)));
                if (type == T_FIN) st ^= 1u << 12;
            } else if (type == T_FIN) {
                const int b = (word >> 4) & 31, q = (word >> 9) & 3;
                float acc[64];
#pragma unroll
                for (int i = 0; i < 64; i++) acc[i] = 0.f;
                const uint32_t s0 = slot;
                reg_fence(acc);
#pragma unroll 1
                for (int i = 0; i < 4; i++) {
                    mbar_wait_c(bar + 8 * (B_FULL_PV + 5 * w + slot), (st >> (5 + slot)) & 1);
                    st ^= 32u << slot;
                    mbar_wait_c(bar + 8 * (B_FINA + i), (st >> 12) & 1);
                    PROF(i == 3 && (threadIdx.x & 127) == 0, 1);
                    const uint32_t da = dlo(sb + OFF_Q + i * 12288, 16), db = dlo(ring + slot * SLOT_BYTES, 16384);
                    wg_fence();
#pragma unroll
                    for (int kk = 0; kk < 8; kk++) wgmma_ss_tb<DH64, DH128>(acc, da + (kk >> 1) * 192 + (kk & 1) * 2, db + kk * 128);
                    wg_commit();
                    slot = wrap5(slot + 1);
                }
                LANE_IDS();
                WAIT_GRANT();
                uint4 pv[8];
                {
                    const uint4* ap = acc_ptr(b, wq < 3 ? wq : 0, q >> 1) + (q & 1) * 256 + ln;
#pragma unroll
                    for (int j = 0; j < 8; j++) pv[j] = __ldcg(ap + j * 32);
                }
                wg_wait<0>();
                reg_fence(acc);
#pragma unroll
                for (int j = 0; j < 8; j++) {
                    acc[8 * j] += __uint_as_float(pv[j].x << 16); acc[8 * j + 1] += __uint_as_float(pv[j].x & 0xffff0000u);
                    acc[8 * j + 2] += __uint_as_float(pv[j].y << 16); acc[8 * j + 3] += __uint_as_float(pv[j].y & 0xffff0000u);
                    acc[8 * j + 4] += __uint_as_float(pv[j].z << 16); acc[8 * j + 5] += __uint_as_float(pv[j].z & 0xffff0000u);
                    acc[8 * j + 6] += __uint_as_float(pv[j].w << 16); acc[8 * j + 7] += __uint_as_float(pv[j].w & 0xffff0000u);
                }
                SET_SLOT(slot);
                st ^= 1u << 12;
                if (lane == 0) {
                    uint32_t s = s0;
                    for (int i = 0; i < 4; i++) { mbar_arrive_n(bar + 8 * (B_EMPTY + s), 3); s = wrap5(s + 1); }
                    for (int i = 0; i < 3; i++) mbar_arrive(bar + 8 * (B_QEMPTY + i));
                }
                if (wq < 3) {
                    __nv_bfloat16* p = P.out + (size_t)(b * SQ + wq * 16 + g8) * 1024 + 512 + q * 128 + 8 * t4;
                    store_frag(acc, p, 1024, 64, t4);
                }
                PROF((threadIdx.x & 127) == 0, 2);
                __syncwarp();
                if (lane == 0) mbar_arrive_n(DONE_BAR, 3);
            } else {
                const bool gqa = (type == T_GQA), tri = (word & 0x4000) != 0, all3 = gqa || tri;
                const uint32_t lead = all3 ? w : word >> 16;
                const bool helper = lead != w;
#define QRDY_BAR (lead == 2 ? 14 : 4 + 4 * lead)
#define MERGE_BAR (lead == 0 ? 15 : 4 * lead - 3)
                float o[64];
                if (helper) {
                    if (!(word & 0x8000)) slot = wrap5(slot + 3);
                    nbar_sync(QRDY_BAR, 256);
                } else if (word & 0x8000) {
                    mbar_wait_c(bar + 8 * (B_QFULL_PV + w), (st >> 10) & 1);
                    st ^= 1u << 10;
                    PROF((threadIdx.x & 127) == 0, 1);
                } else if (!gqa) {
                    const uint32_t fq = bar + 8 * (tri ? B_FULL_SH : B_FULL_PV + 5 * w), sh = tri ? 0 : 5, cq = tri ? 1 : 3;
#pragma unroll
                    for (int i = 0; i < 64; i++) o[i] = 0.f;
#pragma unroll 1
                    for (int i = 0; i < 8; i++) {
                        mbar_wait_c(fq + 8 * slot, (st >> (sh + slot)) & 1);
                        st ^= 1u << (sh + slot);
                        PROF(i == 0 && (threadIdx.x & 127) == 0 && (!tri || w == 0), 1);
                        const uint32_t s = ring + slot * SLOT_BYTES;
                        const uint32_t da = dlo(s + 16384 + (tri ? w * 6144 : 0), 16), db = dlo(s, 8192);
                        wg_fence();
#pragma unroll
                        for (int kk = 0; kk < 4; kk++) wgmma_ss_tb<DH128, DH128>(o, da + kk * 2, db + kk * 128);
                        wg_commit();
                        wg_wait<0>();
                        if (lane == 0) mbar_arrive_n(bar + 8 * (B_EMPTY + slot), cq);
                        slot = wrap5(slot + 1);
                    }
                    reg_fence(o);
                    mbar_wait_c(bar + 8 * (B_QFULL_PV + w), (st >> 10) & 1);
                    st ^= 1u << 10;
                    LANE_IDS();
                    store_q(o, sb + OFF_Q + w * 8192 + (wq * 16 + (ln & 15)) * 128, ln);
                    asm volatile("fence.proxy.async.shared::cta;" ::: "memory");
                    nbar_sync(9 + w, 128);
                    PROF((threadIdx.x & 127) == 0 && (!tri || w == 0), 5);
                } else {
                    float o3[64];
#pragma unroll
                    for (int i = 0; i < 64; i++) { o[i] = 0.f; o3[i] = 0.f; }
#define GQA_Q_LOOP(EXTRA0, EXTRA1)                                                       \
                    _Pragma("unroll 1") for (int i = 0; i < 16; i++) {                   \
                        mbar_wait_c(bar + 8 * (B_FULL_SH + slot), (st >> slot) & 1);     \
                        st ^= 1u << slot;                                                \
                        PROF(i == 0 && threadIdx.x == 0, 1);                             \
                        const uint32_t s = ring + slot * SLOT_BYTES;                     \
                        const uint32_t da = dlo(s + 32768, 16), db = dlo(s + w * 8192, 4096); \
                        wg_fence();                                                      \
                        wgmma_ss_tb<DH64, DH128>(o, da, db);                             \
                        EXTRA0;                                                          \
                        wgmma_ss_tb<DH64, DH128>(o, da + 2, db + 128);                   \
                        EXTRA1;                                                          \
                        wg_commit();                                                     \
                        wg_wait<0>();                                                    \
                        if (lane == 0) mbar_arrive(bar + 8 * (B_EMPTY + slot));          \
                        slot = wrap5(slot + 1);                                          \
                    }
                    if (w == 0) { GQA_Q_LOOP((wgmma_ss_tb<DH64, DH128>(o3, da, db + 1536)), (wgmma_ss_tb<DH64, DH128>(o3, da + 2, db + 1664))) }
                    else { GQA_Q_LOOP((void)0, (void)0) }
                    reg_fence(o);
                    reg_fence(o3);
                    mbar_wait_c(bar + 8 * (B_QFULL_PV + w), (st >> 10) & 1);
                    st ^= 1u << 10;
                    nbar_sync(12, 384);
                    if (wq < 3) {
                        LANE_IDS();
                        const uint32_t qa = sb + OFF_Q + (w * SQ + wq * 16 + (ln & 15)) * 128;
                        store_q(o, qa, ln);
                        if (w == 0) store_q(o3, qa + 3 * SQ * 128, ln);
                        asm volatile("fence.proxy.async.shared::cta;" ::: "memory");
                    }
                    nbar_sync(12, 384);
                    PROF(threadIdx.x == 0, 5);
                }
                if (!all3 && !helper) nbar_arrive(QRDY_BAR, 256);
                const uint32_t fb = bar + 8 * (gqa ? B_FULL_SH : B_FULL_PV + 5 * w), sh = gqa ? 0 : 5, cnt = gqa ? 1 : 3;
                if (all3) st ^= 1u << 13;
#define TOK_ME (1 + w + ((st >> 11) & 4))
#pragma unroll
                for (int i = 0; i < 64; i++) o[i] = 0.f;
                float m0 = -INFINITY, m1 = -INFINITY, l0 = 0.f, l1 = 0.f;
                const float cs = 0.08838834764831845f * 1.4426950408889634f;
                const uint32_t dq = dlo(sb + OFF_Q + lead * 8192, 16);
                const uint32_t rk = tri ? w : helper ? 1 : 0;
                uint32_t ks = wrap5(slot + rk);
                uint32_t vs = wrap5(wrap5(slot + (tri ? 3 : gqa ? 1 : 2)) + 2 * rk);
                SET_SLOT(wrap5(slot + (tri ? 4 : 3)));
                float s[64];
                {
                    const uint32_t dk = __shfl_sync(0xffffffffu, dlo(ring + ks * SLOT_BYTES, 16), 0);
                    mbar_wait_c(fb + 8 * ks, (st >> (sh + ks)) & 1);
                    st ^= 1u << (sh + ks);
                    if (all3 && w > 0) nbar_sync(TOK_ME, 256);
                    wg_fence();
                    wgmma_ss_first<DH128, DHKV>(s, dq, dk);
#pragma unroll
                    for (int kk = 1; kk < 8; kk++) wgmma_ss<DH128, DHKV>(s, dq + (kk >> 2) * 1536 + (kk & 3) * 2, dk + (kk >> 2) * 64 + (kk & 3) * 2);
                    wg_commit();
                    if (all3 && w < 2) nbar_arrive(TOK_ME + 1, 256);
                    wg_wait<0>();
                    reg_fence(s);
                    if (lane == 0) mbar_arrive_n(bar + 8 * (B_EMPTY + ks), cnt);
                }
#pragma unroll 1
                for (int j = all3 ? 0 : 2; j < 4; j++) {
                    TRACE(0);
                    asm volatile("" : "+r"(st));
                    uint32_t pr[32];
                    if (!gqa && wq == 3) {
#pragma unroll
                        for (int i = 0; i < 32; i++) pr[i] = __float_as_uint(s[i]);
                    } else {
                    float xa[4], xb[4];
#pragma unroll
                    for (int i = 0; i < 4; i++) { xa[i] = fmaxf(s[4 * i], s[4 * i + 1]); xb[i] = fmaxf(s[4 * i + 2], s[4 * i + 3]); }
#pragma unroll
                    for (int i = 4; i < 16; i++) {
                        xa[i & 3] = fmaxf(xa[i & 3], fmaxf(s[4 * i], s[4 * i + 1]));
                        xb[i & 3] = fmaxf(xb[i & 3], fmaxf(s[4 * i + 2], s[4 * i + 3]));
                    }
                    float x0 = fmaxf(fmaxf(xa[0], xa[1]), fmaxf(xa[2], xa[3])), x1 = fmaxf(fmaxf(xb[0], xb[1]), fmaxf(xb[2], xb[3]));
                    x0 = fmaxf(x0, __shfl_xor_sync(0xffffffffu, x0, 1));
                    x1 = fmaxf(x1, __shfl_xor_sync(0xffffffffu, x1, 1));
                    x0 = fmaxf(x0, __shfl_xor_sync(0xffffffffu, x0, 2));
                    x1 = fmaxf(x1, __shfl_xor_sync(0xffffffffu, x1, 2));
                    const float n0 = fmaxf(m0, x0), n1 = fmaxf(m1, x1);
                    const float a0 = ex2((m0 - n0) * cs), a1 = ex2((m1 - n1) * cs);
                    m0 = n0; m1 = n1;
                    const float c0 = -n0 * cs, c1 = -n1 * cs;
                    float ra[2] = {l0 * a0, 0.f}, rb[2] = {l1 * a1, 0.f};
#pragma unroll
                    for (int i = 0; i < 16; i++) {
                        const float p0 = ex2(fmaf(s[4 * i], cs, c0)), p1 = ex2(fmaf(s[4 * i + 1], cs, c0));
                        const float p2 = ex2(fmaf(s[4 * i + 2], cs, c1)), p3 = ex2(fmaf(s[4 * i + 3], cs, c1));
                        ra[i & 1] += p0 + p1; rb[i & 1] += p2 + p3;
                        pr[2 * i] = pack_bf16(p0, p1);
                        pr[2 * i + 1] = pack_bf16(p2, p3);
                        o[4 * i] *= a0; o[4 * i + 1] *= a0; o[4 * i + 2] *= a1; o[4 * i + 3] *= a1;
                    }
                    l0 = ra[0] + ra[1]; l1 = rb[0] + rb[1];
                    }
                    ks = wrap5(vs + 1);
                    const uint32_t dv = __shfl_sync(0xffffffffu, dlo(ring + vs * SLOT_BYTES, 1024), 0);
                    const uint32_t dk = __shfl_sync(0xffffffffu, dlo(ring + ks * SLOT_BYTES, 16), 0);
#pragma unroll
                    for (int i = 0; i < 32; i++) asm volatile("" : "+r"(pr[i])::"memory");
                    asm volatile("" : "+f"(l0), "+f"(l1)::"memory");
                    reg_fence(o);
                    TRACE(1);
                    mbar_wait_c(fb + 8 * vs, (st >> (sh + vs)) & 1);
                    st ^= 1u << (sh + vs);
                    TRACE(2);
                    wg_fence();
#pragma unroll
                    for (int kk = 0; kk < 8; kk++) wgmma_rs_tb<DHKV>(o, pr[4 * kk], pr[4 * kk + 1], pr[4 * kk + 2], pr[4 * kk + 3], dv + kk * 256);
                    wg_commit();
                    TRACE(3);
                    const uint32_t kbar = fb + 8 * ks, kpar = (st >> (sh + ks)) & 1, vrel = bar + 8 * (B_EMPTY + vs);
                    bool kok = true;
                    if (j < 3) kok = mbar_test(kbar, kpar);
                    wg_wait<0>();
                    reg_fence(o);
                    if (lane == 0 && !(helper && j == 3)) mbar_arrive_n(vrel, cnt);
                    if (j == 3) break;
                    if (!kok) mbar_wait_c(kbar, kpar);
                    TRACE(5);
                    wg_fence();
                    wgmma_ss_first<DH128, DHKV>(s, dq, dk);
#pragma unroll
                    for (int kk = 1; kk < 8; kk++) wgmma_ss<DH128, DHKV>(s, dq + (kk >> 2) * 1536 + (kk & 3) * 2, dk + (kk >> 2) * 64 + (kk & 3) * 2);
                    wg_commit();
                    TRACE(6);
                    st ^= 1u << (sh + ks);
                    wg_wait<0>();
                    reg_fence(s);
                    TRACE(7);
                    if (lane == 0) {
                        mbar_arrive_n(bar + 8 * (B_EMPTY + ks), cnt);
                        if (j == 2 && all3) mbar_arrive(bar + 8 * (B_QEMPTY + w));
                    }
                    vs = wrap5(vs + (tri ? ((j == 2 && w > 0) ? 4 * w - 4 : 1) : gqa ? 2 : 4 - rk));
                }
                if (!all3) {
                    const uint32_t ms = helper ? vs : wrap5(vs + 1);
                    const uint32_t ma = ring + ms * SLOT_BYTES + (wq * 32 + lane_id()) * 16;
                    if (helper) {
                        nbar_sync(9 + w, 128);
#pragma unroll
                        for (int i = 0; i < 16; i++)
                            asm volatile("st.shared.v4.f32 [%0], {%1, %2, %3, %4};" ::"r"(ma + i * 2048), "f"(o[4 * i]), "f"(o[4 * i + 1]), "f"(o[4 * i + 2]), "f"(o[4 * i + 3]) : "memory");
                        asm volatile("st.shared.v4.f32 [%0], {%1, %2, %3, %4};" ::"r"(ma + 32768), "f"(m0), "f"(m1), "f"(l0), "f"(l1) : "memory");
                        asm volatile("fence.proxy.async.shared::cta;" ::: "memory");
                        nbar_arrive(MERGE_BAR, 256);
                        continue;
                    }
                    nbar_sync(MERGE_BAR, 256);
                    float bm0, bm1, bl0, bl1;
                    asm volatile("ld.shared.v4.f32 {%0, %1, %2, %3}, [%4];" : "=f"(bm0), "=f"(bm1), "=f"(bl0), "=f"(bl1) : "r"(ma + 32768) : "memory");
                    const float n0 = fmaxf(m0, bm0), n1 = fmaxf(m1, bm1);
                    const float fa0 = ex2((m0 - n0) * cs), fa1 = ex2((m1 - n1) * cs), fb0 = ex2((bm0 - n0) * cs), fb1 = ex2((bm1 - n1) * cs);
                    l0 = l0 * fa0 + bl0 * fb0; l1 = l1 * fa1 + bl1 * fb1;
#pragma unroll
                    for (int i = 0; i < 16; i++) {
                        float v0, v1, v2, v3;
                        asm volatile("ld.shared.v4.f32 {%0, %1, %2, %3}, [%4];" : "=f"(v0), "=f"(v1), "=f"(v2), "=f"(v3) : "r"(ma + i * 2048) : "memory");
                        o[4 * i] = o[4 * i] * fa0 + v0 * fb0; o[4 * i + 1] = o[4 * i + 1] * fa0 + v1 * fb0;
                        o[4 * i + 2] = o[4 * i + 2] * fa1 + v2 * fb1; o[4 * i + 3] = o[4 * i + 3] * fa1 + v3 * fb1;
                    }
                    asm volatile("fence.proxy.async.shared::cta;" ::: "memory");
                    __syncwarp();
                    if (lane == 0) { mbar_arrive_n(bar + 8 * (B_EMPTY + ms), 3); mbar_arrive(bar + 8 * (B_QEMPTY + w)); }
                }
                asm volatile("" : "+r"(st));
                WAIT_GRANT();
                if ((gqa || wq < 3) && !(P.dbg & 16)) {
                    LANE_IDS();
                    l0 += __shfl_xor_sync(0xffffffffu, l0, 1);
                    l1 += __shfl_xor_sync(0xffffffffu, l1, 1);
                    l0 += __shfl_xor_sync(0xffffffffu, l0, 2);
                    l1 += __shfl_xor_sync(0xffffffffu, l1, 2);
                    int b = (word >> 4) & 31, q0, blk;
                    if (gqa) { const int hh = warp / 3; q0 = (warp - hh * 3) * 16; blk = (((word >> 9) & 7) % RSA) * 16 + hh * 4; }
                    else { b += tri ? w : 0; q0 = wq * 16; blk = SCR_B0 + (((word >> 9) & 31) % RSB) * 4; }
                    store_frag_perm(o, __fdividef(1.f, l0), __fdividef(1.f, l1), g_scr + (size_t)b * SCR_BATCH + (blk * SQ + q0) * 32 + (ln ^ ((ln >> 3) & 3)) * 8);
                }
                PROF((threadIdx.x & 127) == 0 && (!all3 || w == 2), 2);
                __syncwarp();
                if (lane == 0) mbar_arrive_n(DONE_BAR, all3 ? 1 : 3);
            }
        }
    } else {
        asm volatile("setmaxnreg.dec.sync.aligned.u32 32;");
        if (warp == 12) {
            nbar_sync(0, 512);
            uint32_t word = mbox[0];
            {
                uint32_t* dst = reinterpret_cast<uint32_t*>(sgen + OFF_TABLE);
                const uint32_t* src = reinterpret_cast<const uint32_t*>(P.table);
                for (int i = lane; i < NT_MAX / 2; i += 32) dst[i] = src[i];
            }
            __syncwarp();
            if (lane == 0) {
                uint32_t rr = ((word & 0x4007) == T_MHA || (word & 7) == T_FIN) ? 2 : 0, mbs = 1 | 4, wph = 0;
                mbar_wait(bar + 8 * B_SETUP, 0);
                const uint32_t base = mbox[8] * P.nt - gridDim.x;
                do {
                    uint32_t t, spins = 0;
                    while (!mbar_try(bar + 8 * B_WANT, wph)) {
                        if ((word & 7) == T_FIN) {
                            asm volatile("ld.relaxed.gpu.global.u32 %0, [%1];" : "=r"(t) : "l"(&g_task_ctr[0]) : "memory");
                            if (t - base >= P.nt) break;
                        }
                        if (++spins > (1u << 22)) __trap();
                    }
                    wph ^= 1;
                    asm volatile("atom.relaxed.gpu.global.add.u32 %0, [%1], 1;" : "=r"(t) : "l"(&g_task_ctr[0]) : "memory");
                    t -= base;
                    word = T_END;
                    if (t < P.nt) {
                        word = reinterpret_cast<const uint16_t*>(sgen + OFF_TABLE)[t];
                        if ((word & 0x4007) == T_MHA || (word & 7) == T_FIN) { word |= rr << 16; rr = wrap3(rr + 2); }
                    }
                    const uint32_t mbi = mbs & 3;
                    mbar_wait(bar + 8 * (B_MBEMPTY + mbi), mbs >> 2);
                    mbox[mbi] = word;
                    mbar_arrive(bar + 8 * (B_MBFULL + mbi));
                    mbs = (mbs + 1) & 7;
                } while (word != T_END);
            }
        } else if (warp == 13) {
            nbar_sync(0, 512);
            if (lane == 0) {
                const unsigned long long ticket = atomicAdd(&g_ticket[0], 1ull);
                const uint32_t e1 = (uint32_t)(ticket / gridDim.x) + 1;
                mbox[8] = e1 - 1;
                mbar_arrive(bar + 8 * B_SETUP);
                uint32_t mbs = 0, qeph = 7, tickets = 0;
                while (true) {
                    mbar_wait(bar + 8 * (B_MBFULL + (mbs & 3)), mbs >> 2);
                    const uint32_t word = mbox[mbs & 3];
                    mbar_arrive(bar + 8 * (B_MBEMPTY + (mbs & 3)));
                    const uint32_t grant = bar + 8 * (B_GRANT + (mbs & 3));
                    mbs = (mbs + 1) & 7;
                    const uint32_t type = word & 7, w = word >> 16;
                    if (type == T_END) break;
                    if (type == T_QP) {
                        mbar_arrive(grant);
                    } else if (type == T_OWN) {
                        const int f0 = ((word & 8) ? F_OFB : F_OFA) + ((word >> 4) & 7), nb = (word & 8) ? 28 : 8;
                        for (int k = 0; k < nb; k++) {
                            poll_flag(f0 + k * 8, 4 * e1);
                            tickets++;
                            asm volatile("st.release.cta.shared.u32 [%0], %1;" ::"r"(sb + OFF_MBOX + 36), "r"(tickets) : "memory");
                        }
                        if (word & 8) poll_flag(F_RFA + 6 * 8 + ((word >> 4) & 7), 2 * e1);
                        mbar_arrive(grant);
                    } else if (type != T_FIN) {
                        const int b = (word >> 4) & 31, h = (word >> 9) & 31, cnt = (type == T_GQA || (word & 0x4000)) ? 3 : 1;
                        if (word & 0x8000) { poll_flag(F_QF + ((h - HQ) >> 1) * 8 + (b >> 2), e1); fence_proxy_async_global(); }
                        for (int k = 0; k < cnt; k++) {
                            const uint32_t wi = w + k, f = bar + 8 * (B_QFULL_PV + wi);
                            mbar_wait(bar + 8 * (B_QEMPTY + wi), (qeph >> wi) & 1);
                            qeph ^= 1u << wi;
                            if (word & 0x8000) {
                                mbar_expect(f, 12288);
                                tma2d(sb + OFF_Q + wi * 8192, &P.maps[M_Q], 0, (b * (NH - HQ) + h - HQ) * 2 * SQ, f);
                                tma2d(sb + OFF_Q + 24576 + wi * 8192, &P.maps[M_Q], 0, (b * (NH - HQ) + h - HQ) * 2 * SQ + SQ, f);
                            } else mbar_arrive(f);
                        }
                        if (P.dbg & 8) {
                        } else if (type == T_GQA) {
                            if (h >= RSA) poll_flag(F_RFA + (h - RSA) * 8 + (b >> 2), 2 * e1);
                        } else if (h >= RSB) {
                            poll_flag(F_RFB + (h - RSB) * 8 + (b >> 2), 2 * e1);
                            if (((b + cnt - 1) >> 2) != (b >> 2)) poll_flag(F_RFB + (h - RSB) * 8 + (b >> 2) + 1, 2 * e1);
                        }
                        mbar_arrive(grant);
                    } else {
                        const int b = (word >> 4) & 31;
                        uint32_t todo = 31, spins = 0;
                        bool qfree = false;
                        while (todo) {
                            uint32_t v[5];
                            asm volatile("ld.relaxed.gpu.global.v4.u32 {%0, %1, %2, %3}, [%4];" : "=r"(v[0]), "=r"(v[1]), "=r"(v[2]), "=r"(v[3])
                                         : "l"(&g_flags[(F_FB + b) * 8]) : "memory");
                            asm volatile("ld.relaxed.gpu.global.u32 %0, [%1];" : "=r"(v[4]) : "l"(&g_flags[(F_AF + (b >> 2) * 2 + ((word >> 10) & 1)) * 8]) : "memory");
                            uint32_t rdy = 0;
#pragma unroll
                            for (int i = 0; i < 5; i++) rdy |= ((int32_t)(v[i] - e1) >= 0 ? 1u : 0u) << i;
                            rdy &= todo;
                            if (!qfree && (rdy & 15)) {
                                if ((rdy | 16) == (todo | 16)) for (int i = 0; i < 3; i++) mbar_wait(bar + 8 * (B_QEMPTY + i), (qeph >> i) & 1);
                                qfree = mbar_test(bar + 8 * B_QEMPTY, qeph & 1) && mbar_test(bar + 8 * (B_QEMPTY + 1), (qeph >> 1) & 1) &&
                                        mbar_test(bar + 8 * (B_QEMPTY + 2), (qeph >> 2) & 1);
                                if (!qfree) rdy &= 16;
                            }
                            if (rdy) {
                                todo ^= rdy;
                                asm volatile("fence.acquire.gpu;" ::: "memory");
                                fence_proxy_async_global();
#pragma unroll 1
                                for (int i = 0; i < 4; i++)
                                    if ((rdy >> i) & 1) {
                                        mbar_expect(bar + 8 * (B_FINA + i), 12288);
                                        tma2d(sb + OFF_Q + i * 12288, &P.maps[M_SQ], 0, (b * SCR_BLKS + SCR_B0 + ((28 + i) % RSB) * 4) * 6, bar + 8 * (B_FINA + i));
                                    }
                                if (rdy & 16) mbar_arrive(grant);
                            } else if (++spins > (1u << 21)) __trap();
                        }
                        qeph ^= 7;
                    }
                }
            }
        } else if (warp == 14) {
            nbar_sync(0, 512);
            if (lane == 0) {
                uint32_t mbs = 0;
                while (true) {
                    const uint32_t mbi = mbs & 3;
                    mbar_wait(bar + 8 * (B_MBFULL + mbi), mbs >> 2);
                    const uint32_t word = mbox[mbi];
                    const uint32_t type = word & 7;
                    if (type == T_END) break;
                    mbar_wait(bar + 8 * (B_DONE + mbi), mbs >> 2);
                    if (type != T_FIN && !(type == T_OWN && !(word & 8))) {
                        if (!(P.dbg & 32)) {
                        fence_proxy_async_global();
                        asm volatile("fence.release.gpu;" ::: "memory");
                        }
                        if (type == T_QP) flag_add(F_QF + (((word >> 7) & 15) - HQ / 2) * 8 + ((word >> 4) & 7));
                        else if (type == T_GQA) flag_add(F_OFA + ((word >> 9) & 7) * 8 + ((word >> 6) & 7));
                        else if (type == T_OWN) flag_add(F_AF + ((word >> 4) & 7) * 2 + ((word >> 7) & 1));
                        else {
                            const int b = (word >> 4) & 31, h = (word >> 9) & 31, cnt = (word & 0x4000) ? 3 : 1;
                            for (int k = 0; k < cnt; k++) flag_add(h >= 28 ? F_FB + b + k : F_OFB + h * 8 + ((b + k) >> 2), h >= 28 ? h - 28 : 0);
                        }
                    }
                    mbar_arrive(bar + 8 * (B_MBEMPTY + mbi));
                    mbs = (mbs + 1) & 7;
                }
            }
        } else {
            uint64_t pol;
            asm volatile("createpolicy.fractional.L2::evict_first.b64 %0, 1.0;" : "=l"(pol));
            uint32_t slot = 0, epar = 1, mbs = 0, tickets = 0;
            uint32_t word = __shfl_sync(0xffffffffu, (uint32_t)P.table[blockIdx.x], 0);
#define PTRACE(i) do {} while (0)
#define DST (sb + OFF_RING + slot * SLOT_BYTES)
#define ACQUIRE() mbar_wait(bar + 8 * (B_EMPTY + slot), epar)
#define ADVANCE() do { if (++slot == NSLOT) { slot = 0; epar ^= 1; } } while (0)
#define WANT() mbar_arrive(bar + 8 * B_WANT)
            uint32_t fset = 0, fpar = 0;
#define NOTE(set) do { fpar ^= 1u << ((set) * 5 + slot); fset = (fset & ~(3u << (2 * slot))) | ((set) << (2 * slot)); } while (0)
            nbar_sync(13, 512);
            while (true) {
                const uint32_t type = word & 7;
                if (type == T_END) break;
                const int b = (word >> 4) & 31, h = (word >> 9) & 31;
                if (type == T_MHA || type == T_GQA) {
                    const bool gqa = type == T_GQA, tri = (word & 0x4000) != 0;
                    if (!(word & 0x8000)) {
                        const uint32_t set = (gqa || tri) ? 0 : 1 + (word >> 16), fo = bar + 40 * set;
                        const uint32_t bytes = gqa ? 35840 : tri ? 34816 : 22528, aoff = gqa ? 32768 : 16384;
                        const CUtensorMap* mw = &P.maps[gqa ? M_WQA : M_WQB];
                        const CUtensorMap* mx = &P.maps[gqa ? M_XA : tri ? M_XB3 : M_XB1];
                        const int n = gqa ? 16 : 8, kstep = gqa ? 32 : 64, c2 = gqa ? h * 8 : h * 2;
#pragma unroll 1
                        for (int i = 0; i < n; i++) {
                            const uint32_t f = fo + 8 * slot, dst = DST;
                            ACQUIRE();
                            if (elect_one()) {
                                {
                                mbar_expect(f, bytes);
                                if ((EXPM & 8) && b >= (gqa ? 30 : 28)) tma3d_h(dst, mw, i * kstep, c2, f, pol);
                                else tma3d(dst, mw, i * kstep, c2, f);
                                tma3d(dst + aoff, mx, b * SQ, i, f);
                                }
                            }
                            NOTE(set);
                            ADVANCE();
                        }
                    }
                    const CUtensorMap* mk = &P.maps[gqa ? M_KA : M_KB];
                    const int row0 = (b * (gqa ? 8 : 32) + h) * (SK / 8), n = tri ? 24 : 8, want = gqa ? -1 : n - P.grab;
                    const uint32_t cap2 = gqa ? P.capg : tri ? P.capt : h >= 28 ? (b >= P.bq ? 10 : P.capq) : P.caps;
#pragma unroll 1
                    for (int i = 0; i < n; i++) {
                        const uint32_t u = tri ? tri_pos(i) : gqa ? i : (0x73652140u >> (4 * i)) & 7;
                        const uint32_t set = gqa ? 0 : tri ? 1 + (u >> 3) : 1 + wrap3((word >> 16) + (u >> 2));
                        const uint32_t f = bar + 8 * (5 * set + slot), dst = DST;
                        const int row = row0 + (u >> 3) * (32 * SK / 8) + ((u & 7) >> 1) * 16;
                        const uint32_t cap = (cap2 + (i & 1)) >> 1;
                        if (cap < NSLOT) {
                            const uint32_t ps = wrap5(slot + NSLOT - cap), pb = ((fset >> (2 * ps)) & 3) * 5 + ps;
                            mbar_wait(bar + 8 * pb, ((fpar >> pb) & 1) ^ 1);
                        }
                        ACQUIRE();
                        if (elect_one()) {
                            mbar_expect(f, 32768);
                            tma_stream(dst, mk + (u & 1), row, f, pol);
                            if (i == want) WANT();
                            PTRACE(i);
                        }
                        NOTE(set);
                        ADVANCE();
                    }
                    if (gqa) {
                        ACQUIRE();
                        if (elect_one()) WANT();
                    }
                } else if (type == T_QP) {
#pragma unroll 1
                    for (int i = 0; i < 16; i++) {
                        const uint32_t f = bar + 8 * (B_FULL_SH + slot), dst = DST;
                        ACQUIRE();
                        if (elect_one()) {
                            mbar_expect(f, 28672);
                            tma3d(dst, &P.maps[M_WQP], i * 32, ((word >> 7) & 15) * 4, f);
                            tma3d(dst + 16384, &P.maps[M_XP], (b & 7) * 192, i, f);
                            if (i == 14) WANT();
                        }
                        NOTE(0u);
                        ADVANCE();
                    }
                } else if (type == T_OWN) {
                    const uint32_t br = (word >> 3) & 1;
                    const int n = br ? 112 : 128, blk0 = br ? SCR_B0 : 0, blk1 = br ? SCR_BLKS : SCR_B0;
                    int blk = blk0;
#pragma unroll 1
                    for (int i = 0; i < n; i++) {
                        if ((i & (br ? 3 : 15)) == 0) {
                            tickets++;
                            uint32_t v, c = 0;
                            while (true) {
                                asm volatile("ld.acquire.cta.shared.u32 %0, [%1];" : "=r"(v) : "r"(sb + OFF_MBOX + 36) : "memory");
                                if (v >= tickets) break;
                                if (++c > (1u << 23)) __trap();
                                __nanosleep(32);
                            }
                            fence_proxy_async_global();
                        }
                        const uint32_t f = bar + 8 * (B_FULL_SH + slot), dst = DST;
                        ACQUIRE();
                        if (elect_one()) {
                            {
                            mbar_expect(f, 28672);
                            if ((EXPM & 2) && (b & 7) >= 6) tma5d_h(dst, &P.maps[M_WOA + br], 0, i * 4, ((word >> 7) & 1) * 4, f, pol);
                            else tma5d(dst, &P.maps[M_WOA + br], 0, i * 4, ((word >> 7) & 1) * 4, f);
                            if (EXPM & 1) tma3d_h(dst + 16384, &P.maps[M_SA], blk * 6, (b & 7) * 4, f, pol);
                            else tma3d(dst + 16384, &P.maps[M_SA], blk * 6, (b & 7) * 4, f);
                            }
                            if (i == n - 3) WANT();
                        }
                        if (++blk == blk1) blk = blk0;
                        NOTE(0u);
                        ADVANCE();
                    }
                } else {
#pragma unroll 1
                    for (int i = 0; i < 4; i++) {
                        const uint32_t f = bar + 8 * (B_FULL_PV + 5 * (word >> 16) + slot), dst = DST;
                        ACQUIRE();
                        if (elect_one()) {
                            mbar_expect(f, 32768);
                            tma5d(dst, &P.maps[M_WOF], (h & 3) * 128, 0, (28 + i) * 4, f);
                            tma5d(dst + 16384, &P.maps[M_WOF], (h & 3) * 128 + 64, 0, (28 + i) * 4, f);
                        }
                        NOTE(1 + (word >> 16));
                        ADVANCE();
                    }
                    mbar_wait(bar + 8 * (B_EMPTY + (slot == 0 ? NSLOT - 1 : slot - 1)), slot == 0 ? epar : epar ^ 1);
                    if (elect_one()) WANT();
                }
                if (elect_one()) mbar_arrive(bar + 8 * (B_MBEMPTY + (mbs & 3)));
                mbs = (mbs + 1) & 7;
                mbar_wait(bar + 8 * (B_MBFULL + (mbs & 3)), mbs >> 2);
                word = __shfl_sync(0xffffffffu, mbox[mbs & 3], 0);
            }
        }
    }
}

struct Knobs {
    float a0;
    float a1;
    float owna, ownb;
    float finlag;
    float single;
    float grab, s0, qp0, qpd, capt, caps, capq, capg, bq, dbg, grid, pkv, pw;
};
Knobs KN = {0.5f, 24.0f, 5.f, 6.5f, 4.0f, 25.f, 3.f, 2.f, 18.f, 0.2f, 4.f, 3.f, 2.f, 3.f, 32.f, 0.f, 0.f, 2.f, 2.f};

typedef CUresult (*EncodeFn)(CUtensorMap*, CUtensorMapDataType, cuuint32_t, void*, const cuuint64_t*, const cuuint64_t*,
                             const cuuint32_t*, const cuuint32_t*, CUtensorMapInterleave, CUtensorMapSwizzle,
                             CUtensorMapL2promotion, CUtensorMapFloatOOBfill);

void enc(EncodeFn fn, CUtensorMap* m, const void* ptr, int rank, uint64_t d0, uint64_t d1, uint64_t d2, uint64_t s1, uint64_t s2,
         uint32_t b0, uint32_t b1, uint32_t b2, CUtensorMapSwizzle sw) {
    cuuint64_t dims[3] = {d0, d1, d2};
    cuuint64_t strides[2] = {s1, s2};
    cuuint32_t box[3] = {b0, b1, b2};
    cuuint32_t es[3] = {1, 1, 1};
    fn(m, CU_TENSOR_MAP_DATA_TYPE_BFLOAT16, rank, const_cast<void*>(ptr), dims, strides, box, es, CU_TENSOR_MAP_INTERLEAVE_NONE, sw,
       (CUtensorMapL2promotion)(int)KN.pw, CU_TENSOR_MAP_FLOAT_OOB_FILL_NONE);
}

int build_table(uint16_t* table) {
    static float key[NT_MAX];
    static uint16_t word[NT_MAX];
    static int idx[NT_MAX];
    int n = 0;
    for (int h = 0; h < 28; h++)
        for (int b = 0; b < 32;) {
            const bool tri = h < HQ && h + b / 32.f < KN.single && h + b / 32.f >= KN.s0 && b + 3 <= 32 && !(b == 15);
            key[n] = h + b / 32.f;
            word[n++] = (uint16_t)(T_MHA | 8 | (b << 4) | (h << 9) | (tri ? 0x4000 : 0) | (h >= HQ ? 0x8000 : 0));
            b += tri ? 3 : 1;
        }
    for (int j = HQ / 2; j < 16; j++)
        for (int g = 0; g < 8; g++) {
            key[n] = KN.qp0 + ((j - HQ / 2) * 8 + g) * KN.qpd;
            word[n++] = (uint16_t)(T_QP | (g << 4) | (j << 7));
        }
    for (int b = 0; b < 32; b++)
        for (int q = 0; q < 4; q++) {
            key[n] = 28.f + (b * 4 + q) / 32.f;
            word[n++] = (uint16_t)(T_MHA | 8 | (b << 4) | ((28 + q) << 9) | (28 + q >= HQ ? 0x8000 : 0));
            key[n] = 28.f + (b * 4 + 4 + q) / 32.f + KN.finlag;
            word[n++] = (uint16_t)(T_FIN | 8 | (b << 4) | (q << 9));
        }
    const float da = (KN.a1 - KN.a0) / 256.f;
    for (int r = 0; r < 8; r++)
        for (int g = 0; g < 8; g++) {
            const float ka = KN.a0 + (r * 32 + g * 4) * da;
            for (int i = 0; i < 4; i++) {
                key[n] = ka + i * da + 0.001f;
                word[n++] = (uint16_t)(T_GQA | ((g * 4 + i) << 4) | (r << 9));
            }
        }
    for (int i = 0; i < 32; i++) {
        key[n] = (i < 16 ? KN.ownb : KN.owna) + i * 0.001f;
        word[n++] = (uint16_t)(T_OWN | ((1 - (i >> 4)) << 3) | (((i >> 1) & 7) << 4) | ((i & 1) << 7));
    }
    {
        const int dbg = (int)KN.dbg;
        int m = 0;
        for (int i = 0; i < n; i++) {
            const int ty = word[i] & 7;
            if ((ty == T_GQA && (dbg & 2)) || (ty == T_MHA && (dbg & 4)) || ((ty == T_OWN || ty == T_FIN) && (dbg & 8))) continue;
            key[m] = key[i]; word[m++] = word[i];
        }
        n = m;
    }
    for (int i = 0; i < n; i++) idx[i] = i;
    for (int i = 1; i < n; i++) {
        const int v = idx[i];
        int j = i - 1;
        while (j >= 0 && key[idx[j]] > key[v]) { idx[j + 1] = idx[j]; j--; }
        idx[j + 1] = v;
    }
    for (int i = 0; i < n; i++) table[i] = word[idx[i]];
    for (int i = n; i < NT_MAX; i++) table[i] = T_END;
    return n;
}

}

extern "C" void kernel_launch(void* const* d_in, const int* in_sizes, int n_in, void* d_out, int out_size) {
    (void)in_sizes; (void)n_in; (void)out_size;
    static Params P;
    static int nsm = 0;
    void* fnp = nullptr;
    cudaDriverEntryPointQueryResult qr;
    cudaGetDriverEntryPoint("cuTensorMapEncodeTiled", &fnp, cudaEnableDefault, &qr);
    EncodeFn fn = (EncodeFn)fnp;
    void* scr = nullptr;
    void* qs = nullptr;
    cudaGetSymbolAddress(&scr, g_scr);
    cudaGetSymbolAddress(&qs, g_q);
    const CUtensorMapSwizzle S128 = CU_TENSOR_MAP_SWIZZLE_128B, S64 = CU_TENSOR_MAP_SWIZZLE_64B;
    for (int i = 0; i < 4; i++) {
        cuuint64_t dims[4] = {64, 8, 2, (cuuint64_t)NB * (i < 2 ? 8 : NH) * (SK / 8)}, strides[3] = {256, 128, 2048};
        cuuint32_t box[4] = {64, 8, 2, 16}, es[4] = {1, 1, 1, 1};
        fn(&P.maps[M_KA + i], CU_TENSOR_MAP_DATA_TYPE_BFLOAT16, 4, d_in[i < 2 ? 1 + i : 4 + i], dims, strides, box, es, CU_TENSOR_MAP_INTERLEAVE_NONE, S128,
           (CUtensorMapL2promotion)(int)KN.pkv, CU_TENSOR_MAP_FLOAT_OOB_FILL_NONE);
    }
    enc(fn, &P.maps[M_XA], d_in[0], 3, 32, NTOK, 16, DM * 2, 64, 32, 48, 1, S64);
    enc(fn, &P.maps[M_XB3], d_in[5], 3, 64, NTOK, 8, DM * 2, 128, 64, 144, 1, S128);
    enc(fn, &P.maps[M_XB1], d_in[5], 3, 64, NTOK, 8, DM * 2, 128, 64, 48, 1, S128);
    enc(fn, &P.maps[M_WQA], d_in[3], 3, 64, DM, 64, NH * DH * 2, 128, 64, 32, 8, S128);
    enc(fn, &P.maps[M_WQB], d_in[8], 3, 64, DM, 64, NH * DH * 2, 128, 64, 64, 2, S128);
    for (int i = 0; i < 3; i++) {
        const bool fin = i == 2;
        cuuint64_t dims[5] = {fin ? 512u : 64u, 2, fin ? 4u : 512u, 4, fin ? 128u : 8u};
        cuuint64_t strides[4] = {1024, 8 * 1024, 2 * 1024, fin ? 32u * 1024u : 128u};
        cuuint32_t box[5] = {64, 2, 4, 4, 4}, es[5] = {1, 1, 1, 1, 1};
        fn(&P.maps[M_WOA + i], CU_TENSOR_MAP_DATA_TYPE_BFLOAT16, 5, d_in[i ? 9 : 4], dims, strides, box, es, CU_TENSOR_MAP_INTERLEAVE_NONE, S128,
           (CUtensorMapL2promotion)(int)KN.pw, CU_TENSOR_MAP_FLOAT_OOB_FILL_NONE);
    }
    enc(fn, &P.maps[M_SA], scr, 3, 256, SCR_BLKS * 6, NB, 512, SCR_BATCH * 2, 256, 6, 4, CU_TENSOR_MAP_SWIZZLE_NONE);
    enc(fn, &P.maps[M_SQ], scr, 2, 256, NB * SCR_BLKS * 6, 1, 512, 0, 256, 24, 1, CU_TENSOR_MAP_SWIZZLE_NONE);
    enc(fn, &P.maps[M_WQP], d_in[8], 3, 64, DM, 64, NH * DH * 2, 128, 64, 32, 4, S128);
    enc(fn, &P.maps[M_XP], d_in[5], 3, 32, NTOK, 16, DM * 2, 64, 32, 192, 1, S64);
    enc(fn, &P.maps[M_Q], qs, 2, 64, NB * (NH - HQ) * 2 * SQ + 64, 1, 128, 0, 64, SQ, 1, S128);
    P.out = (__nv_bfloat16*)d_out;
    P.nt = (uint32_t)build_table(P.table);
    P.grab = (int)KN.grab; P.bq = (int)KN.bq; P.capt = (int)(2 * KN.capt); P.caps = (int)(2 * KN.caps); P.capq = (int)(2 * KN.capq); P.capg = (int)(2 * KN.capg); P.dbg = (int)KN.dbg;
    if (nsm == 0) {
        int dev = 0;
        cudaGetDevice(&dev);
        cudaDeviceGetAttribute(&nsm, cudaDevAttrMultiProcessorCount, dev);
        cudaFuncSetAttribute(fused_attn_kernel, cudaFuncAttributeMaxDynamicSharedMemorySize, SMEM_BYTES);
    }
    fused_attn_kernel<<<KN.grid > 0 ? (int)KN.grid : nsm, 512, SMEM_BYTES>>>(P);
}
```

```cpp
#include <cuda_runtime.h>
#include <cuda_bf16.h>
#include <cuda.h>
#include <stdint.h>

#define K_RSA 2
#define K_RSB 7
#define EXPM 1
#define K_HQ 32

namespace {

constexpr int NB = 32, SQ = 48, DM = 512, NH = 32, SK = 512, DH = 128;
constexpr int NTOK = NB * SQ;
constexpr int RSA = K_RSA;
constexpr int RSB = K_RSB;
constexpr int SCR_B0 = RSA * 16;
constexpr int SCR_BLKS = SCR_B0 + RSB * 4;
constexpr int SCR_BATCH = SCR_BLKS * SQ * 32;
constexpr int HQ = K_HQ;
constexpr int NSLOT = 5;
constexpr int SLOT_BYTES = 35840;
constexpr int QBUF_BYTES = 49152;
constexpr int NT_MAX = 1200;

enum : uint32_t { T_QP = 0, T_MHA = 1, T_GQA = 2, T_OWN = 3, T_FIN = 4, T_END = 5 };

enum { M_KA, M_VA, M_KB, M_VB, M_XA, M_XB3, M_XB1, M_WQA, M_WQB, M_WOA, M_WOB, M_WOF, M_SA, M_SQ, M_WQP, M_XP, M_Q, M_COUNT };

struct Params {
    CUtensorMap maps[M_COUNT];
    __nv_bfloat16* out;
    uint32_t nt;
    int grab, flo, fmod, bq, capz;
    uint32_t capt, caps, capq, capg;
    int dbg;
    uint16_t table[NT_MAX];
};

constexpr int F_QF = 0;
constexpr int F_OFA = 64;
constexpr int F_RFA = 128;
constexpr int F_OFB = 192;
constexpr int F_RFB = 448;
constexpr int F_FB = 720;
constexpr int F_COUNT = 752;

__device__ __align__(1024) __nv_bfloat16 g_scr[NB * SCR_BATCH];
__device__ __align__(1024) __nv_bfloat16 g_q[NB * (NH - HQ) * SQ * DH + 8192];
__device__ __align__(128) unsigned int g_flags[F_COUNT * 8];
__device__ __align__(128) unsigned int g_task_ctr[32];
__device__ __align__(128) unsigned long long g_ticket[16];
#define PROF(cond, k) do {} while (0)
#define TRACE(k) do {} while (0)

constexpr int OFF_Q = 0;
constexpr int OFF_RING = QBUF_BYTES;
constexpr int OFF_BAR = OFF_RING + NSLOT * SLOT_BYTES;
constexpr int B_FULL_SH = 0;
constexpr int B_FULL_PV = 5;
constexpr int B_EMPTY = 20;
constexpr int B_QFULL_PV = 25;
constexpr int B_QEMPTY = 29;
constexpr int B_GRANT = 32;
constexpr int B_MBFULL = 36;
constexpr int B_MBEMPTY = 40;
constexpr int B_DONE = 44;
constexpr int B_SETUP = 48;
constexpr int B_WANT = 49;
constexpr int B_FINA = 50;
constexpr int B_LAST = 53;
constexpr int OFF_MBOX = OFF_BAR + 512;
constexpr int OFF_TABLE = OFF_MBOX + 64;
constexpr int SMEM_BYTES = OFF_TABLE + NT_MAX * 2 + 1024;

constexpr uint32_t DH128 = (1024u >> 4) | (1u << 30);
constexpr uint32_t DH64 = (512u >> 4) | (2u << 30);
constexpr uint32_t DHKV = (2048u >> 4) | (1u << 30);

__device__ __forceinline__ uint32_t smem_u32(const void* p) { return (uint32_t)__cvta_generic_to_shared(p); }
__device__ __forceinline__ void mbar_init(uint32_t a, uint32_t c) { asm volatile("mbarrier.init.shared::cta.b64 [%0], %1;" ::"r"(a), "r"(c)); }
__device__ __forceinline__ void mbar_expect(uint32_t a, uint32_t bytes) { asm volatile("mbarrier.arrive.expect_tx.shared::cta.b64 _, [%0], %1;" ::"r"(a), "r"(bytes) : "memory"); }
__device__ __forceinline__ void mbar_arrive(uint32_t a) { asm volatile("mbarrier.arrive.shared::cta.b64 _, [%0];" ::"r"(a) : "memory"); }
__device__ __forceinline__ void mbar_arrive_n(uint32_t a, uint32_t n) { asm volatile("mbarrier.arrive.shared::cta.b64 _, [%0], %1;" ::"r"(a), "r"(n) : "memory"); }
__device__ __forceinline__ bool mbar_try(uint32_t a, uint32_t parity) {
    uint32_t ok;
    asm volatile("{\n.reg .pred p;\nmbarrier.try_wait.parity.shared::cta.b64 p, [%1], %2;\nselp.u32 %0, 1, 0, p;\n}\n" : "=r"(ok) : "r"(a), "r"(parity) : "memory");
    return ok != 0;
}
__device__ __forceinline__ bool mbar_test(uint32_t a, uint32_t parity) {
    uint32_t ok;
    asm volatile("{\n.reg .pred p;\nmbarrier.test_wait.parity.shared::cta.b64 p, [%1], %2;\nselp.u32 %0, 1, 0, p;\n}\n" : "=r"(ok) : "r"(a), "r"(parity) : "memory");
    return ok != 0;
}
__device__ __forceinline__ void mbar_wait(uint32_t a, uint32_t parity) {
    uint32_t n = 0;
    while (!mbar_try(a, parity)) { if (++n > (1u << 22)) __trap(); }
}
__device__ __forceinline__ void mbar_wait_c(uint32_t a, uint32_t parity) {
    while (!mbar_try(a, parity)) {}
}
__device__ __forceinline__ void tma2d(uint32_t dst, const CUtensorMap* m, int c0, int c1, uint32_t bar) {
    asm volatile("cp.async.bulk.tensor.2d.shared::cluster.global.mbarrier::complete_tx::bytes [%0], [%1, {%3, %4}], [%2];"
                 ::"r"(dst), "l"(m), "r"(bar), "r"(c0), "r"(c1) : "memory");
}
__device__ __forceinline__ void tma3d(uint32_t dst, const CUtensorMap* m, int c1, int c2, uint32_t bar) {
    asm volatile("cp.async.bulk.tensor.3d.shared::cluster.global.mbarrier::complete_tx::bytes [%0], [%1, {%3, %4, %5}], [%2];"
                 ::"r"(dst), "l"(m), "r"(bar), "r"(0), "r"(c1), "r"(c2) : "memory");
}
__device__ __forceinline__ void tma3d_h(uint32_t dst, const CUtensorMap* m, int c1, int c2, uint32_t bar, uint64_t pol) {
    asm volatile("cp.async.bulk.tensor.3d.shared::cluster.global.mbarrier::complete_tx::bytes.L2::cache_hint [%0], [%1, {%3, %4, %5}], [%2], %6;"
                 ::"r"(dst), "l"(m), "r"(bar), "r"(0), "r"(c1), "r"(c2), "l"(pol) : "memory");
}
__device__ __forceinline__ void tma5d_h(uint32_t dst, const CUtensorMap* m, int c0, int c2, int c4, uint32_t bar, uint64_t pol) {
    asm volatile("cp.async.bulk.tensor.5d.shared::cluster.global.mbarrier::complete_tx::bytes.L2::cache_hint [%0], [%1, {%4, %3, %5, %3, %6}], [%2], %7;"
                 ::"r"(dst), "l"(m), "r"(bar), "r"(0), "r"(c0), "r"(c2), "r"(c4), "l"(pol) : "memory");
}
__device__ __forceinline__ void tma5d(uint32_t dst, const CUtensorMap* m, int c0, int c2, int c4, uint32_t bar) {
    asm volatile("cp.async.bulk.tensor.5d.shared::cluster.global.mbarrier::complete_tx::bytes [%0], [%1, {%4, %3, %5, %3, %6}], [%2];"
                 ::"r"(dst), "l"(m), "r"(bar), "r"(0), "r"(c0), "r"(c2), "r"(c4) : "memory");
}
__device__ __forceinline__ void tma_stream(uint32_t dst, const CUtensorMap* m, int c1, uint32_t bar, uint64_t pol) {
    asm volatile("cp.async.bulk.tensor.4d.shared::cluster.global.mbarrier::complete_tx::bytes.L2::cache_hint [%0], [%1, {%3, %3, %3, %4}], [%2], %5;"
                 ::"r"(dst), "l"(m), "r"(bar), "r"(0), "r"(c1), "l"(pol) : "memory");
}
__device__ __forceinline__ bool elect_one() {
    uint32_t p;
    asm volatile("{\n.reg .pred p;\nelect.sync _|p, 0xffffffff;\nselp.u32 %0, 1, 0, p;\n}\n" : "=r"(p));
    return p != 0;
}
__device__ __forceinline__ int lane_id() { int l; asm volatile("mov.u32 %0, %%laneid;" : "=r"(l)); return l; }
__device__ __forceinline__ uint32_t tri_pos(int i) {
    if (i < 3) return i << 3;
    if (i >= 21) return ((i - 21) << 3) | 7;
    const int v = i - 3, j = (v * 43) >> 8, c = v - 6 * j;
    return ((c >> 1) << 3) | (2 * j + 1 + (c & 1));
}
__device__ __forceinline__ void fence_proxy_async_global() { asm volatile("fence.proxy.async.global;" ::: "memory"); }
__device__ __forceinline__ void poll_flag(int idx, uint32_t target) {
    const unsigned int* p = &g_flags[idx * 8];
    uint32_t n = 0;
    while (true) {
        uint32_t v;
        asm volatile("ld.relaxed.gpu.global.u32 %0, [%1];" : "=r"(v) : "l"(p) : "memory");
        if ((int32_t)(v - target) >= 0) break;
        if (++n > (1u << 21)) __trap();
        __nanosleep(64);
    }
    asm volatile("fence.acquire.gpu;" ::: "memory");
}
__device__ __forceinline__ void flag_add(int idx, uint32_t v = 1) {
    asm volatile("red.relaxed.gpu.global.add.u32 [%0], %1;" ::"l"(&g_flags[idx * 8]), "r"(v) : "memory");
}
__device__ __forceinline__ void wg_fence() { asm volatile("wgmma.fence.sync.aligned;" ::: "memory"); }
__device__ __forceinline__ void wg_commit() { asm volatile("wgmma.commit_group.sync.aligned;" ::: "memory"); }
template <int N> __device__ __forceinline__ void wg_wait() { asm volatile("wgmma.wait_group.sync.aligned %0;" ::"n"(N) : "memory"); }
template <int N> __device__ __forceinline__ void reg_fence(float (&d)[N]) {
#pragma unroll
    for (int i = 0; i < N; i++) asm volatile("" : "+f"(d[i])::"memory");
}
__device__ __forceinline__ void nbar_sync(uint32_t id, uint32_t n) { asm volatile("barrier.cta.sync %0, %1;" ::"r"(id), "r"(n) : "memory"); }
__device__ __forceinline__ void nbar_arrive(uint32_t id, uint32_t n) { asm volatile("barrier.cta.arrive %0, %1;" ::"r"(id), "r"(n) : "memory"); }
__device__ __forceinline__ uint32_t dlo(uint32_t addr, uint32_t lbo) { return (addr >> 4) | ((lbo >> 4) << 16); }
__device__ __forceinline__ uint32_t pack_bf16(float lo, float hi) {
    uint32_t r;
    asm("cvt.rn.bf16x2.f32 %0, %1, %2;" : "=r"(r) : "f"(hi), "f"(lo));
    return r;
}
__device__ __forceinline__ float ex2(float x) { float y; asm("ex2.approx.ftz.f32 %0, %1;" : "=f"(y) : "f"(x)); return y; }
__device__ __forceinline__ uint32_t wrap3(uint32_t s) { return s >= 3 ? s - 3 : s; }
__device__ __forceinline__ uint32_t wrap5(uint32_t s) { return s >= NSLOT ? s - NSLOT : s; }
__device__ __forceinline__ uint4 quad_transpose(uint32_t v0, uint32_t v1, uint32_t v2, uint32_t v3, int t) {
    const bool o1 = t & 1, o2 = t & 2;
    uint32_t s0 = __shfl_xor_sync(0xffffffffu, o1 ? v0 : v1, 1);
    uint32_t s1 = __shfl_xor_sync(0xffffffffu, o1 ? v2 : v3, 1);
    uint32_t a0 = o1 ? s0 : v0, a1 = o1 ? v1 : s0, b0 = o1 ? s1 : v2, b1 = o1 ? v3 : s1;
    uint32_t r0 = __shfl_xor_sync(0xffffffffu, o2 ? a0 : b0, 2);
    uint32_t r1 = __shfl_xor_sync(0xffffffffu, o2 ? a1 : b1, 2);
    uint4 o;
    o.x = o2 ? r0 : a0; o.y = o2 ? r1 : a1; o.z = o2 ? b0 : r0; o.w = o2 ? b1 : r1;
    return o;
}
__device__ __forceinline__ void store_frag(const float (&d)[64], __nv_bfloat16* p, int ld, int js, int t) {
#pragma unroll
    for (int j = 0; j < 16; j += 4) {
        uint4 lo = quad_transpose(pack_bf16(d[4 * j], d[4 * j + 1]), pack_bf16(d[4 * j + 4], d[4 * j + 5]),
                                  pack_bf16(d[4 * j + 8], d[4 * j + 9]), pack_bf16(d[4 * j + 12], d[4 * j + 13]), t);
        uint4 hi = quad_transpose(pack_bf16(d[4 * j + 2], d[4 * j + 3]), pack_bf16(d[4 * j + 6], d[4 * j + 7]),
                                  pack_bf16(d[4 * j + 10], d[4 * j + 11]), pack_bf16(d[4 * j + 14], d[4 * j + 15]), t);
        *reinterpret_cast<uint4*>(p + (j & 4) * 8 + (j >> 3) * js) = lo;
        *reinterpret_cast<uint4*>(p + (j & 4) * 8 + (j >> 3) * js + 8 * ld) = hi;
    }
}
__device__ __forceinline__ void store_q(const float (&d)[64], uint32_t qa, int ln) {
#pragma unroll
    for (int j = 0; j < 16; j += 2) {
        const uint32_t a = qa + (j >> 3) * 24576 + ((((j + (ln >> 4)) & 7) ^ (ln & 7)) << 4);
        asm volatile("stmatrix.sync.aligned.m8n8.x4.shared.b16 [%0], {%1, %2, %3, %4};" ::"r"(a), "r"(pack_bf16(d[4 * j], d[4 * j + 1])),
                     "r"(pack_bf16(d[4 * j + 2], d[4 * j + 3])), "r"(pack_bf16(d[4 * j + 4], d[4 * j + 5])), "r"(pack_bf16(d[4 * j + 6], d[4 * j + 7])) : "memory");
    }
}
__device__ __forceinline__ void st16(__nv_bfloat16* p, uint32_t a, uint32_t b, uint32_t c, uint32_t d) {
    if (EXPM & 4) {
        uint64_t pol;
        asm("createpolicy.fractional.L2::evict_first.b64 %0, 1.0;" : "=l"(pol));
        asm volatile("st.global.L2::cache_hint.v4.u32 [%0], {%1, %2, %3, %4}, %5;" ::"l"(p), "r"(a), "r"(b), "r"(c), "r"(d), "l"(pol) : "memory");
    } else *reinterpret_cast<uint4*>(p) = make_uint4(a, b, c, d);
}
__device__ __forceinline__ void store_frag_perm(const float (&d)[64], float s0, float s1, __nv_bfloat16* p) {
#pragma unroll
    for (int j = 0; j < 16; j += 4) {
        st16(p + (j >> 2) * (SQ * 32), pack_bf16(d[4 * j] * s0, d[4 * j + 1] * s0), pack_bf16(d[4 * j + 4] * s0, d[4 * j + 5] * s0),
             pack_bf16(d[4 * j + 8] * s0, d[4 * j + 9] * s0), pack_bf16(d[4 * j + 12] * s0, d[4 * j + 13] * s0));
        st16(p + (j >> 2) * (SQ * 32) + 256, pack_bf16(d[4 * j + 2] * s1, d[4 * j + 3] * s1), pack_bf16(d[4 * j + 6] * s1, d[4 * j + 7] * s1),
             pack_bf16(d[4 * j + 10] * s1, d[4 * j + 11] * s1), pack_bf16(d[4 * j + 14] * s1, d[4 * j + 15] * s1));
    }
}
__device__ __forceinline__ uint4* acc_ptr(int b, int rb, int nh) {
    return reinterpret_cast<uint4*>(g_scr + (size_t)b * SCR_BATCH + (6 % RSA) * 16 * SQ * 32) + (rb * 2 + nh) * 512;
}
__device__ __forceinline__ void acc_store(const float (&d)[64], uint4* ap) {
#pragma unroll
    for (int j = 0; j < 8; j++)
        ap[j * 32] = make_uint4(pack_bf16(d[8 * j], d[8 * j + 1]), pack_bf16(d[8 * j + 2], d[8 * j + 3]), pack_bf16(d[8 * j + 4], d[8 * j + 5]),
                                pack_bf16(d[8 * j + 6], d[8 * j + 7]));
}

template <uint32_t AH, uint32_t BH>
__device__ __forceinline__ void wgmma_ss(float (&d)[64], uint32_t da, uint32_t db) {
    asm volatile("{\n.reg .pred p;\n.reg .b64 a, b;\n.reg .b32 x, y;\nsetp.eq.b32 p, 0, 0;\nmov.b32 x, %66;\nmov.b32 y, %67;\nmov.b64 a, {%64, x};\nmov.b64 b, {%65, y};\n"
        "wgmma.mma_async.sync.aligned.m64n128k16.f32.bf16.bf16 "
        "{%0, %1, %2, %3, %4, %5, %6, %7, %8, %9, %10, %11, %12, %13, %14, %15, %16, %17, %18, %19, %20, %21, %22, %23, "
        "%24, %25, %26, %27, %28, %29, %30, %31, %32, %33, %34, %35, %36, %37, %38, %39, %40, %41, %42, %43, %44, %45, "
        "%46, %47, %48, %49, %50, %51, %52, %53, %54, %55, %56, %57, %58, %59, %60, %61, %62, %63}, "
        "a, b, p, 1, 1, 0, 0;\n}\n"
        : "+f"(d[0]), "+f"(d[1]), "+f"(d[2]), "+f"(d[3]), "+f"(d[4]), "+f"(d[5]), "+f"(d[6]), "+f"(d[7]), "+f"(d[8]),
          "+f"(d[9]), "+f"(d[10]), "+f"(d[11]), "+f"(d[12]), "+f"(d[13]), "+f"(d[14]), "+f"(d[15]), "+f"(d[16]),
          "+f"(d[17]), "+f"(d[18]), "+f"(d[19]), "+f"(d[20]), "+f"(d[21]), "+f"(d[22]), "+f"(d[23]), "+f"(d[24]),
          "+f"(d[25]), "+f"(d[26]), "+f"(d[27]), "+f"(d[28]), "+f"(d[29]), "+f"(d[30]), "+f"(d[31]), "+f"(d[32]),
          "+f"(d[33]), "+f"(d[34]), "+f"(d[35]), "+f"(d[36]), "+f"(d[37]), "+f"(d[38]), "+f"(d[39]), "+f"(d[40]),
          "+f"(d[41]), "+f"(d[42]), "+f"(d[43]), "+f"(d[44]), "+f"(d[45]), "+f"(d[46]), "+f"(d[47]), "+f"(d[48]),
          "+f"(d[49]), "+f"(d[50]), "+f"(d[51]), "+f"(d[52]), "+f"(d[53]), "+f"(d[54]), "+f"(d[55]), "+f"(d[56]),
          "+f"(d[57]), "+f"(d[58]), "+f"(d[59]), "+f"(d[60]), "+f"(d[61]), "+f"(d[62]), "+f"(d[63])
        : "r"(da), "r"(db), "n"(AH), "n"(BH));
}

template <uint32_t AH, uint32_t BH>
__device__ __forceinline__ void wgmma_ss_first(float (&d)[64], uint32_t da, uint32_t db) {
    asm volatile("{\n.reg .pred p;\n.reg .b64 a, b;\n.reg .b32 x, y;\nsetp.ne.b32 p, 0, 0;\nmov.b32 x, %66;\nmov.b32 y, %67;\nmov.b64 a, {%64, x};\nmov.b64 b, {%65, y};\n"
        "wgmma.mma_async.sync.aligned.m64n128k16.f32.bf16.bf16 "
        "{%0, %1, %2, %3, %4, %5, %6, %7, %8, %9, %10, %11, %12, %13, %14, %15, %16, %17, %18, %19, %20, %21, %22, %23, "
        "%24, %25, %26, %27, %28, %29, %30, %31, %32, %33, %34, %35, %36, %37, %38, %39, %40, %41, %42, %43, %44, %45, "
        "%46, %47, %48, %49, %50, %51, %52, %53, %54, %55, %56, %57, %58, %59, %60, %61, %62, %63}, "
        "a, b, p, 1, 1, 0, 0;\n}\n"
        : "=f"(d[0]), "=f"(d[1]), "=f"(d[2]), "=f"(d[3]), "=f"(d[4]), "=f"(d[5]), "=f"(d[6]), "=f"(d[7]), "=f"(d[8]),
          "=f"(d[9]), "=f"(d[10]), "=f"(d[11]), "=f"(d[12]), "=f"(d[13]), "=f"(d[14]), "=f"(d[15]), "=f"(d[16]),
          "=f"(d[17]), "=f"(d[18]), "=f"(d[19]), "=f"(d[20]), "=f"(d[21]), "=f"(d[22]), "=f"(d[23]), "=f"(d[24]),
          "=f"(d[25]), "=f"(d[26]), "=f"(d[27]), "=f"(d[28]), "=f"(d[29]), "=f"(d[30]), "=f"(d[31]), "=f"(d[32]),
          "=f"(d[33]), "=f"(d[34]), "=f"(d[35]), "=f"(d[36]), "=f"(d[37]), "=f"(d[38]), "=f"(d[39]), "=f"(d[40]),
          "=f"(d[41]), "=f"(d[42]), "=f"(d[43]), "=f"(d[44]), "=f"(d[45]), "=f"(d[46]), "=f"(d[47]), "=f"(d[48]),
          "=f"(d[49]), "=f"(d[50]), "=f"(d[51]), "=f"(d[52]), "=f"(d[53]), "=f"(d[54]), "=f"(d[55]), "=f"(d[56]),
          "=f"(d[57]), "=f"(d[58]), "=f"(d[59]), "=f"(d[60]), "=f"(d[61]), "=f"(d[62]), "=f"(d[63])
        : "r"(da), "r"(db), "n"(AH), "n"(BH));
}

template <uint32_t AH, uint32_t BH>
__device__ __forceinline__ void wgmma_ss_tb(float (&d)[64], uint32_t da, uint32_t db) {
    asm volatile("{\n.reg .pred p;\n.reg .b64 a, b;\n.reg .b32 x, y;\nsetp.eq.b32 p, 0, 0;\nmov.b32 x, %66;\nmov.b32 y, %67;\nmov.b64 a, {%64, x};\nmov.b64 b, {%65, y};\n"
        "wgmma.mma_async.sync.aligned.m64n128k16.f32.bf16.bf16 "
        "{%0, %1, %2, %3, %4, %5, %6, %7, %8, %9, %10, %11, %12, %13, %14, %15, %16, %17, %18, %19, %20, %21, %22, %23, "
        "%24, %25, %26, %27, %28, %29, %30, %31, %32, %33, %34, %35, %36, %37, %38, %39, %40, %41, %42, %43, %44, %45, "
        "%46, %47, %48, %49, %50, %51, %52, %53, %54, %55, %56, %57, %58, %59, %60, %61, %62, %63}, "
        "a, b, p, 1, 1, 0, 1;\n}\n"
        : "+f"(d[0]), "+f"(d[1]), "+f"(d[2]), "+f"(d[3]), "+f"(d[4]), "+f"(d[5]), "+f"(d[6]), "+f"(d[7]), "+f"(d[8]),
          "+f"(d[9]), "+f"(d[10]), "+f"(d[11]), "+f"(d[12]), "+f"(d[13]), "+f"(d[14]), "+f"(d[15]), "+f"(d[16]),
          "+f"(d[17]), "+f"(d[18]), "+f"(d[19]), "+f"(d[20]), "+f"(d[21]), "+f"(d[22]), "+f"(d[23]), "+f"(d[24]),
          "+f"(d[25]), "+f"(d[26]), "+f"(d[27]), "+f"(d[28]), "+f"(d[29]), "+f"(d[30]), "+f"(d[31]), "+f"(d[32]),
          "+f"(d[33]), "+f"(d[34]), "+f"(d[35]), "+f"(d[36]), "+f"(d[37]), "+f"(d[38]), "+f"(d[39]), "+f"(d[40]),
          "+f"(d[41]), "+f"(d[42]), "+f"(d[43]), "+f"(d[44]), "+f"(d[45]), "+f"(d[46]), "+f"(d[47]), "+f"(d[48]),
          "+f"(d[49]), "+f"(d[50]), "+f"(d[51]), "+f"(d[52]), "+f"(d[53]), "+f"(d[54]), "+f"(d[55]), "+f"(d[56]),
          "+f"(d[57]), "+f"(d[58]), "+f"(d[59]), "+f"(d[60]), "+f"(d[61]), "+f"(d[62]), "+f"(d[63])
        : "r"(da), "r"(db), "n"(AH), "n"(BH));
}

template <uint32_t BH>
__device__ __forceinline__ void wgmma_rs_tb(float (&d)[64], uint32_t a0, uint32_t a1, uint32_t a2, uint32_t a3, uint32_t db) {
    asm volatile("{\n.reg .pred p;\n.reg .b64 b;\n.reg .b32 y;\nsetp.eq.b32 p, 0, 0;\nmov.b32 y, %69;\nmov.b64 b, {%68, y};\n"
        "wgmma.mma_async.sync.aligned.m64n128k16.f32.bf16.bf16 "
        "{%0, %1, %2, %3, %4, %5, %6, %7, %8, %9, %10, %11, %12, %13, %14, %15, %16, %17, %18, %19, %20, %21, %22, %23, "
        "%24, %25, %26, %27, %28, %29, %30, %31, %32, %33, %34, %35, %36, %37, %38, %39, %40, %41, %42, %43, %44, %45, "
        "%46, %47, %48, %49, %50, %51, %52, %53, %54, %55, %56, %57, %58, %59, %60, %61, %62, %63}, "
        "{%64, %65, %66, %67}, b, p, 1, 1, 1;\n}\n"
        : "+f"(d[0]), "+f"(d[1]), "+f"(d[2]), "+f"(d[3]), "+f"(d[4]), "+f"(d[5]), "+f"(d[6]), "+f"(d[7]), "+f"(d[8]),
          "+f"(d[9]), "+f"(d[10]), "+f"(d[11]), "+f"(d[12]), "+f"(d[13]), "+f"(d[14]), "+f"(d[15]), "+f"(d[16]),
          "+f"(d[17]), "+f"(d[18]), "+f"(d[19]), "+f"(d[20]), "+f"(d[21]), "+f"(d[22]), "+f"(d[23]), "+f"(d[24]),
          "+f"(d[25]), "+f"(d[26]), "+f"(d[27]), "+f"(d[28]), "+f"(d[29]), "+f"(d[30]), "+f"(d[31]), "+f"(d[32]),
          "+f"(d[33]), "+f"(d[34]), "+f"(d[35]), "+f"(d[36]), "+f"(d[37]), "+f"(d[38]), "+f"(d[39]), "+f"(d[40]),
          "+f"(d[41]), "+f"(d[42]), "+f"(d[43]), "+f"(d[44]), "+f"(d[45]), "+f"(d[46]), "+f"(d[47]), "+f"(d[48]),
          "+f"(d[49]), "+f"(d[50]), "+f"(d[51]), "+f"(d[52]), "+f"(d[53]), "+f"(d[54]), "+f"(d[55]), "+f"(d[56]),
          "+f"(d[57]), "+f"(d[58]), "+f"(d[59]), "+f"(d[60]), "+f"(d[61]), "+f"(d[62]), "+f"(d[63])
        : "r"(a0), "r"(a1), "r"(a2), "r"(a3), "r"(db), "n"(BH));
}

__global__ void __launch_bounds__(512, 1) fused_attn_kernel(const __grid_constant__ Params P) {
    extern __shared__ uint8_t smem_raw[];
    const uint32_t sb = (smem_u32(smem_raw) + 1023u) & ~1023u;
    uint8_t* sgen = smem_raw + (sb - smem_u32(smem_raw));
    const uint32_t bar = sb + OFF_BAR;
    volatile uint32_t* mbox = reinterpret_cast<volatile uint32_t*>(sgen + OFF_MBOX);
    const int warp = __shfl_sync(0xffffffffu, threadIdx.x >> 5, 0), lane = threadIdx.x & 31;

    if (lane == 0) {
#pragma unroll 1
        for (int i = warp; i <= B_LAST; i += 16)
            mbar_init(bar + 8 * i, ((i >= B_EMPTY && i < B_QFULL_PV) || (i >= B_DONE && i < B_SETUP)) ? 12 : (i >= B_QEMPTY && i < B_GRANT) ? 4
                                   : (i >= B_MBEMPTY && i < B_DONE) ? 15 : 1);
        if (warp == B_MBFULL - 32) { mbox[0] = P.table[blockIdx.x]; mbox[4] = blockIdx.x; mbox[9] = 0; mbar_arrive(bar + 8 * B_MBFULL); }
        asm volatile("fence.mbarrier_init.release.cluster;" ::: "memory");
        asm volatile("fence.proxy.async.shared::cta;" ::: "memory");
    }
    __syncwarp();
    nbar_arrive(warp == 15 ? 0 : 13, 512);

    if (warp < 12) {
        asm volatile("setmaxnreg.inc.sync.aligned.u32 160;");
        nbar_sync(0, 512);
        const uint32_t w = warp >> 2, wq = warp & 3;
        uint32_t st = 0;
        const uint32_t ring = sb + OFF_RING;
#define MB_ADDR(base) (bar + 8 * (base) + ((st >> 13) & 24))
#define MB_PAR ((st >> 18) & 1)
#define DONE_BAR MB_ADDR(B_DONE)
#define WAIT_GRANT() mbar_wait_c(MB_ADDR(B_GRANT), MB_PAR)
#define SET_SLOT(x) st = (st & ~(7u << 20)) | ((x) << 20)
        for (;; st = (st & ~(7u << 16)) | ((st + (1u << 16)) & (7u << 16))) {
            asm volatile("" : "+r"(st));
            mbar_wait_c(MB_ADDR(B_MBFULL), MB_PAR);
            const uint32_t word = __shfl_sync(0xffffffffu, mbox[(st >> 16) & 3], 0);
            if (lane == 0) mbar_arrive(MB_ADDR(B_MBEMPTY));
            uint32_t slot = st >> 20;
            const uint32_t type = word & 7;
            if (type == T_END) break;
#define LANE_IDS() const int ln = lane_id(); const int g8 = ln >> 2, t4 = ln & 3; (void)g8; (void)t4

            if (type == T_OWN || type == T_QP) {
                float acc0[64], acc1[64];
#pragma unroll
                for (int i = 0; i < 64; i++) { acc0[i] = 0.f; acc1[i] = 0.f; }
                const uint32_t br = (word >> 3) & 1, g = (word >> 4) & 7, nh = (word >> 7) & 1;
                const int n = type == T_QP ? 16 : br ? 112 : 128;
                const uint32_t bmask = type == T_QP ? 255 : br ? 3 : 15;
#pragma unroll 1
                for (int i = 0; i < n; i++) {
                    mbar_wait_c(bar + 8 * (B_FULL_SH + slot), (st >> slot) & 1);
                    st ^= 1u << slot;
                    PROF(i == 0 && threadIdx.x == 0, 1);
                    const uint32_t s = ring + slot * SLOT_BYTES;
                    const uint32_t da = dlo(s + 16384 + w * 4096, 16), db = dlo(s, 4096);
                    wg_fence();
                    wgmma_ss_tb<DH64, DH128>(acc0, da, db);
                    wgmma_ss_tb<DH64, DH128>(acc1, da, db + 512);
                    wgmma_ss_tb<DH64, DH128>(acc0, da + 2, db + 128);
                    wgmma_ss_tb<DH64, DH128>(acc1, da + 2, db + 640);
                    wg_commit();
                    if ((i & bmask) == bmask && threadIdx.x == 0) flag_add((br ? F_RFB + (i >> 2) * 8 : F_RFA + (i >> 4) * 8) + g);
                    wg_wait<0>();
                    if (lane == 0) mbar_arrive(bar + 8 * (B_EMPTY + slot));
                    slot = wrap5(slot + 1);
                }
                reg_fence(acc0);
                reg_fence(acc1);
                SET_SLOT(slot);
                asm volatile("" : "+r"(st));
                PROF(threadIdx.x == 0, 5);
                LANE_IDS();
                if (br) {
                    WAIT_GRANT();
                    uint4* ap = acc_ptr(g * 4 + warp / 3, warp % 3, nh) + ln;
                    acc_store(acc0, ap);
                    acc_store(acc1, ap + 256);
                } else {
                    const bool qp = type == T_QP;
                    const int bb = warp / 3, ld = qp ? 64 : 1024, js = qp ? SQ * 64 : 64;
                    __nv_bfloat16* p = qp ? g_q + (size_t)((g * 4 + bb) * (NH - HQ) + ((word >> 7) & 15) * 2 - HQ) * (SQ * DH) + ((warp - bb * 3) * 16 + g8) * 64 + 8 * t4
                                          : P.out + (size_t)(g * 192 + warp * 16 + g8) * 1024 + nh * 256 + 8 * t4;
                    store_frag(acc0, p, ld, js, t4);
                    store_frag(acc1, p + 2 * js, ld, js, t4);
                }
                PROF(threadIdx.x == 0, 2);
                __syncwarp();
                if (lane == 0) mbar_arrive(DONE_BAR);
            } else if (type == T_FIN ? (word >> 16) != w : (type == T_MHA && !(word & 0x4000) && wrap3((word >> 16) + 2) == w)) {
                SET_SLOT(wrap5(slot + (type == T_FIN ? 4 : (word & 0x8000) ? 3 : 1)));
                if (type == T_FIN) st ^= 1u << 12;
            } else if (type == T_FIN) {
                const int b = (word >> 4) & 31, q = (word >> 9) & 3;
                float acc[64];
#pragma unroll
                for (int i = 0; i < 64; i++) acc[i] = 0.f;
                const uint32_t s0 = slot;
                reg_fence(acc);
#define FIN_STEP(i)                                                                                                  \
                {                                                                                                        \
                    mbar_wait_c(bar + 8 * (B_FINA + (i)), (st >> 12) & 1);                                               \
                    PROF((i) == 3 && (threadIdx.x & 127) == 0, 1);                                                       \
                    const uint32_t ws = wrap5(s0 + __shfl_sync(0xffffffffu, mbox[12 + (i)], 0));                         \
                    mbar_wait_c(bar + 8 * (B_FULL_PV + 5 * w + ws), (st >> (5 + ws)) & 1);                               \
                    st ^= 32u << ws;                                                                                     \
                    const uint32_t da = dlo(sb + OFF_Q + (i) * 12288, 16), db = dlo(ring + ws * SLOT_BYTES, 16384);      \
                    wg_fence();                                                                                          \
                    _Pragma("unroll") for (int kk = 0; kk < 8; kk++)                                                     \
                        wgmma_ss_tb<DH64, DH128>(acc, da + (kk >> 1) * 192 + (kk & 1) * 2, db + kk * 128);               \
                    wg_commit();                                                                                         \
                }
#pragma unroll 1
                for (int i = 0; i < 3; i++) FIN_STEP(i)
                LANE_IDS();
                WAIT_GRANT();
                uint4 pv[8];
                {
                    const uint4* ap = acc_ptr(b, wq < 3 ? wq : 0, q >> 1) + (q & 1) * 256 + ln;
#pragma unroll
                    for (int j = 0; j < 8; j++) pv[j] = __ldcg(ap + j * 32);
                }
                FIN_STEP(3)
                wg_wait<0>();
                reg_fence(acc);
#pragma unroll
                for (int j = 0; j < 8; j++) {
                    acc[8 * j] += __uint_as_float(pv[j].x << 16); acc[8 * j + 1] += __uint_as_float(pv[j].x & 0xffff0000u);
                    acc[8 * j + 2] += __uint_as_float(pv[j].y << 16); acc[8 * j + 3] += __uint_as_float(pv[j].y & 0xffff0000u);
                    acc[8 * j + 4] += __uint_as_float(pv[j].z << 16); acc[8 * j + 5] += __uint_as_float(pv[j].z & 0xffff0000u);
                    acc[8 * j + 6] += __uint_as_float(pv[j].w << 16); acc[8 * j + 7] += __uint_as_float(pv[j].w & 0xffff0000u);
                }
                SET_SLOT(wrap5(s0 + 4));
                st ^= 1u << 12;
                if (lane == 0) {
                    uint32_t s = s0;
                    for (int i = 0; i < 4; i++) { mbar_arrive_n(bar + 8 * (B_EMPTY + s), 3); s = wrap5(s + 1); }
                    for (int i = 0; i < 3; i++) mbar_arrive(bar + 8 * (B_QEMPTY + i));
                }
                if (wq < 3) {
                    __nv_bfloat16* p = P.out + (size_t)(b * SQ + wq * 16 + g8) * 1024 + 512 + q * 128 + 8 * t4;
                    store_frag(acc, p, 1024, 64, t4);
                }
                PROF((threadIdx.x & 127) == 0, 2);
                __syncwarp();
                if (lane == 0) mbar_arrive_n(DONE_BAR, 3);
            } else {
                const bool gqa = (type == T_GQA), tri = (word & 0x4000) != 0, all3 = gqa || tri;
                const uint32_t lead = all3 ? w : word >> 16;
                const bool helper = lead != w;
#define QRDY_BAR (lead == 2 ? 14 : 4 + 4 * lead)
#define MERGE_BAR (lead == 0 ? 15 : 4 * lead - 3)
                float o[64];
                if (helper) {
                    if (!(word & 0x8000)) slot = wrap5(slot + 3);
                    nbar_sync(QRDY_BAR, 256);
                } else if (word & 0x8000) {
                    mbar_wait_c(bar + 8 * (B_QFULL_PV + w), (st >> 10) & 1);
                    st ^= 1u << 10;
                    PROF((threadIdx.x & 127) == 0, 1);
                } else if (!gqa) {
                    const uint32_t fq = bar + 8 * (tri ? B_FULL_SH : B_FULL_PV + 5 * w), sh = tri ? 0 : 5, cq = tri ? 1 : 3;
#pragma unroll
                    for (int i = 0; i < 64; i++) o[i] = 0.f;
#pragma unroll 1
                    for (int i = 0; i < 8; i++) {
                        mbar_wait_c(fq + 8 * slot, (st >> (sh + slot)) & 1);
                        st ^= 1u << (sh + slot);
                        PROF(i == 0 && (threadIdx.x & 127) == 0 && (!tri || w == 0), 1);
                        const uint32_t s = ring + slot * SLOT_BYTES;
                        const uint32_t da = dlo(s + 16384 + (tri ? w * 6144 : 0), 16), db = dlo(s, 8192);
                        wg_fence();
#pragma unroll
                        for (int kk = 0; kk < 4; kk++) wgmma_ss_tb<DH128, DH128>(o, da + kk * 2, db + kk * 128);
                        wg_commit();
                        wg_wait<0>();
                        if (lane == 0) mbar_arrive_n(bar + 8 * (B_EMPTY + slot), cq);
                        slot = wrap5(slot + 1);
                    }
                    reg_fence(o);
                    mbar_wait_c(bar + 8 * (B_QFULL_PV + w), (st >> 10) & 1);
                    st ^= 1u << 10;
                    LANE_IDS();
                    store_q(o, sb + OFF_Q + w * 8192 + (wq * 16 + (ln & 15)) * 128, ln);
                    asm volatile("fence.proxy.async.shared::cta;" ::: "memory");
                    nbar_sync(9 + w, 128);
                    PROF((threadIdx.x & 127) == 0 && (!tri || w == 0), 5);
                } else {
                    float o3[64];
#pragma unroll
                    for (int i = 0; i < 64; i++) { o[i] = 0.f; o3[i] = 0.f; }
#define GQA_Q_LOOP(EXTRA0, EXTRA1)                                                       \
                    _Pragma("unroll 1") for (int i = 0; i < 16; i++) {                   \
                        mbar_wait_c(bar + 8 * (B_FULL_SH + slot), (st >> slot) & 1);     \
                        st ^= 1u << slot;                                                \
                        PROF(i == 0 && threadIdx.x == 0, 1);                             \
                        const uint32_t s = ring + slot * SLOT_BYTES;                     \
                        const uint32_t da = dlo(s + 32768, 16), db = dlo(s + w * 8192, 4096); \
                        wg_fence();                                                      \
                        wgmma_ss_tb<DH64, DH128>(o, da, db);                             \
                        EXTRA0;                                                          \
                        wgmma_ss_tb<DH64, DH128>(o, da + 2, db + 128);                   \
                        EXTRA1;                                                          \
                        wg_commit();                                                     \
                        wg_wait<0>();                                                    \
                        if (lane == 0) mbar_arrive(bar + 8 * (B_EMPTY + slot));          \
                        slot = wrap5(slot + 1);                                          \
                    }
                    if (w == 0) { GQA_Q_LOOP((wgmma_ss_tb<DH64, DH128>(o3, da, db + 1536)), (wgmma_ss_tb<DH64, DH128>(o3, da + 2, db + 1664))) }
                    else { GQA_Q_LOOP((void)0, (void)0) }
                    reg_fence(o);
                    reg_fence(o3);
                    mbar_wait_c(bar + 8 * (B_QFULL_PV + w), (st >> 10) & 1);
                    st ^= 1u << 10;
                    nbar_sync(12, 384);
                    if (wq < 3) {
                        LANE_IDS();
                        const uint32_t qa = sb + OFF_Q + (w * SQ + wq * 16 + (ln & 15)) * 128;
                        store_q(o, qa, ln);
                        if (w == 0) store_q(o3, qa + 3 * SQ * 128, ln);
                        asm volatile("fence.proxy.async.shared::cta;" ::: "memory");
                    }
                    nbar_sync(12, 384);
                    PROF(threadIdx.x == 0, 5);
                }
                if (!all3 && !helper) nbar_arrive(QRDY_BAR, 256);
                const uint32_t fb = bar + 8 * (gqa ? B_FULL_SH : B_FULL_PV + 5 * w), sh = gqa ? 0 : 5, cnt = gqa ? 1 : 3;
                if (all3) st ^= 1u << 13;
#define TOK_ME (1 + w + ((st >> 11) & 4))
#pragma unroll
                for (int i = 0; i < 64; i++) o[i] = 0.f;
                float m0 = -INFINITY, m1 = -INFINITY, l0 = 0.f, l1 = 0.f;
                const float cs = 0.08838834764831845f * 1.4426950408889634f;
                const uint32_t dq = dlo(sb + OFF_Q + lead * 8192, 16);
                const uint32_t rk = tri ? w : (gqa || helper) ? 0 : 1;
                uint32_t ks = wrap5(slot + rk);
                uint32_t vs = wrap5(wrap5(slot + (tri ? 3 : gqa ? 1 : 2)) + 2 * rk);
                SET_SLOT(wrap5(slot + (tri ? 4 : 3)));
                float s[64];
                {
                    const uint32_t dk = __shfl_sync(0xffffffffu, dlo(ring + ks * SLOT_BYTES, 16), 0);
                    mbar_wait_c(fb + 8 * ks, (st >> (sh + ks)) & 1);
                    st ^= 1u << (sh + ks);
                    if (all3 && w > 0) nbar_sync(TOK_ME, 256);
                    wg_fence();
                    wgmma_ss_first<DH128, DHKV>(s, dq, dk);
#pragma unroll
                    for (int kk = 1; kk < 8; kk++) wgmma_ss<DH128, DHKV>(s, dq + (kk >> 2) * 1536 + (kk & 3) * 2, dk + (kk >> 2) * 64 + (kk & 3) * 2);
                    wg_commit();
                    if (all3 && w < 2) nbar_arrive(TOK_ME + 1, 256);
                    wg_wait<0>();
                    reg_fence(s);
                    if (lane == 0) mbar_arrive_n(bar + 8 * (B_EMPTY + ks), cnt);
                }
#pragma unroll 1
                for (int j = all3 ? 0 : 2; j < 4; j++) {
                    TRACE(0);
                    asm volatile("" : "+r"(st));
                    uint32_t pr[32];
                    if (!gqa && wq == 3) {
#pragma unroll
                        for (int i = 0; i < 32; i++) pr[i] = __float_as_uint(s[i]);
                    } else {
                    float xa[4], xb[4];
#pragma unroll
                    for (int i = 0; i < 4; i++) { xa[i] = fmaxf(s[4 * i], s[4 * i + 1]); xb[i] = fmaxf(s[4 * i + 2], s[4 * i + 3]); }
#pragma unroll
                    for (int i = 4; i < 16; i++) {
                        xa[i & 3] = fmaxf(xa[i & 3], fmaxf(s[4 * i], s[4 * i + 1]));
                        xb[i & 3] = fmaxf(xb[i & 3], fmaxf(s[4 * i + 2], s[4 * i + 3]));
                    }
                    float x0 = fmaxf(fmaxf(xa[0], xa[1]), fmaxf(xa[2], xa[3])), x1 = fmaxf(fmaxf(xb[0], xb[1]), fmaxf(xb[2], xb[3]));
                    x0 = fmaxf(x0, __shfl_xor_sync(0xffffffffu, x0, 1));
                    x1 = fmaxf(x1, __shfl_xor_sync(0xffffffffu, x1, 1));
                    x0 = fmaxf(x0, __shfl_xor_sync(0xffffffffu, x0, 2));
                    x1 = fmaxf(x1, __shfl_xor_sync(0xffffffffu, x1, 2));
                    const float n0 = fmaxf(m0, x0), n1 = fmaxf(m1, x1);
                    const float a0 = ex2((m0 - n0) * cs), a1 = ex2((m1 - n1) * cs);
                    m0 = n0; m1 = n1;
                    const float c0 = -n0 * cs, c1 = -n1 * cs;
                    float ra[2] = {l0 * a0, 0.f}, rb[2] = {l1 * a1, 0.f};
#pragma unroll
                    for (int i = 0; i < 16; i++) {
                        const float p0 = ex2(fmaf(s[4 * i], cs, c0)), p1 = ex2(fmaf(s[4 * i + 1], cs, c0));
                        const float p2 = ex2(fmaf(s[4 * i + 2], cs, c1)), p3 = ex2(fmaf(s[4 * i + 3], cs, c1));
                        ra[i & 1] += p0 + p1; rb[i & 1] += p2 + p3;
                        pr[2 * i] = pack_bf16(p0, p1);
                        pr[2 * i + 1] = pack_bf16(p2, p3);
                        o[4 * i] *= a0; o[4 * i + 1] *= a0; o[4 * i + 2] *= a1; o[4 * i + 3] *= a1;
                    }
                    l0 = ra[0] + ra[1]; l1 = rb[0] + rb[1];
                    }
                    ks = wrap5(vs + 1);
                    const uint32_t dv = __shfl_sync(0xffffffffu, dlo(ring + vs * SLOT_BYTES, 1024), 0);
                    const uint32_t dk = __shfl_sync(0xffffffffu, dlo(ring + ks * SLOT_BYTES, 16), 0);
#pragma unroll
                    for (int i = 0; i < 32; i++) asm volatile("" : "+r"(pr[i])::"memory");
                    asm volatile("" : "+f"(l0), "+f"(l1)::"memory");
                    reg_fence(o);
                    TRACE(1);
                    mbar_wait_c(fb + 8 * vs, (st >> (sh + vs)) & 1);
                    st ^= 1u << (sh + vs);
                    TRACE(2);
                    wg_fence();
#pragma unroll
                    for (int kk = 0; kk < 8; kk++) wgmma_rs_tb<DHKV>(o, pr[4 * kk], pr[4 * kk + 1], pr[4 * kk + 2], pr[4 * kk + 3], dv + kk * 256);
                    wg_commit();
                    TRACE(3);
                    const uint32_t kbar = fb + 8 * ks, kpar = (st >> (sh + ks)) & 1, vrel = bar + 8 * (B_EMPTY + vs);
                    bool kok = true;
                    if (j < 3) kok = mbar_test(kbar, kpar);
                    wg_wait<0>();
                    reg_fence(o);
                    if (lane == 0 && !(helper && j == 3)) mbar_arrive_n(vrel, cnt);
                    if (j == 3) break;
                    if (!kok) mbar_wait_c(kbar, kpar);
                    TRACE(5);
                    wg_fence();
                    wgmma_ss_first<DH128, DHKV>(s, dq, dk);
#pragma unroll
                    for (int kk = 1; kk < 8; kk++) wgmma_ss<DH128, DHKV>(s, dq + (kk >> 2) * 1536 + (kk & 3) * 2, dk + (kk >> 2) * 64 + (kk & 3) * 2);
                    wg_commit();
                    TRACE(6);
                    st ^= 1u << (sh + ks);
                    wg_wait<0>();
                    reg_fence(s);
                    TRACE(7);
                    if (lane == 0) {
                        mbar_arrive_n(bar + 8 * (B_EMPTY + ks), cnt);
                        if (j == 2 && all3) mbar_arrive(bar + 8 * (B_QEMPTY + w));
                    }
                    vs = wrap5(vs + (tri ? ((j == 2 && w > 0) ? 4 * w - 4 : 1) : gqa ? 2 : 4 - rk));
                }
                if (!all3) {
                    const uint32_t ms = helper ? vs : wrap5(vs + 4);
                    const uint32_t ma = ring + ms * SLOT_BYTES + (wq * 32 + lane_id()) * 16;
                    if (helper) {
                        nbar_sync(9 + w, 128);
#pragma unroll
                        for (int i = 0; i < 16; i++)
                            asm volatile("st.shared.v4.f32 [%0], {%1, %2, %3, %4};" ::"r"(ma + i * 2048), "f"(o[4 * i]), "f"(o[4 * i + 1]), "f"(o[4 * i + 2]), "f"(o[4 * i + 3]) : "memory");
                        asm volatile("st.shared.v4.f32 [%0], {%1, %2, %3, %4};" ::"r"(ma + 32768), "f"(m0), "f"(m1), "f"(l0), "f"(l1) : "memory");
                        asm volatile("fence.proxy.async.shared::cta;" ::: "memory");
                        nbar_arrive(MERGE_BAR, 256);
                        continue;
                    }
                    nbar_sync(MERGE_BAR, 256);
                    float bm0, bm1, bl0, bl1;
                    asm volatile("ld.shared.v4.f32 {%0, %1, %2, %3}, [%4];" : "=f"(bm0), "=f"(bm1), "=f"(bl0), "=f"(bl1) : "r"(ma + 32768) : "memory");
                    const float n0 = fmaxf(m0, bm0), n1 = fmaxf(m1, bm1);
                    const float fa0 = ex2((m0 - n0) * cs), fa1 = ex2((m1 - n1) * cs), fb0 = ex2((bm0 - n0) * cs), fb1 = ex2((bm1 - n1) * cs);
                    l0 = l0 * fa0 + bl0 * fb0; l1 = l1 * fa1 + bl1 * fb1;
#pragma unroll
                    for (int i = 0; i < 16; i++) {
                        float v0, v1, v2, v3;
                        asm volatile("ld.shared.v4.f32 {%0, %1, %2, %3}, [%4];" : "=f"(v0), "=f"(v1), "=f"(v2), "=f"(v3) : "r"(ma + i * 2048) : "memory");
                        o[4 * i] = o[4 * i] * fa0 + v0 * fb0; o[4 * i + 1] = o[4 * i + 1] * fa0 + v1 * fb0;
                        o[4 * i + 2] = o[4 * i + 2] * fa1 + v2 * fb1; o[4 * i + 3] = o[4 * i + 3] * fa1 + v3 * fb1;
                    }
                    asm volatile("fence.proxy.async.shared::cta;" ::: "memory");
                    __syncwarp();
                    if (lane == 0) { mbar_arrive_n(bar + 8 * (B_EMPTY + ms), 3); mbar_arrive(bar + 8 * (B_QEMPTY + w)); }
                }
                asm volatile("" : "+r"(st));
                WAIT_GRANT();
                if ((gqa || wq < 3) && !(P.dbg & 16)) {
                    LANE_IDS();
                    l0 += __shfl_xor_sync(0xffffffffu, l0, 1);
                    l1 += __shfl_xor_sync(0xffffffffu, l1, 1);
                    l0 += __shfl_xor_sync(0xffffffffu, l0, 2);
                    l1 += __shfl_xor_sync(0xffffffffu, l1, 2);
                    int b = (word >> 4) & 31, q0, blk;
                    if (gqa) { const int hh = warp / 3; q0 = (warp - hh * 3) * 16; blk = (((word >> 9) & 7) % RSA) * 16 + hh * 4; }
                    else { b += tri ? w : 0; q0 = wq * 16; blk = SCR_B0 + (((word >> 9) & 31) % RSB) * 4; }
                    store_frag_perm(o, __fdividef(1.f, l0), __fdividef(1.f, l1), g_scr + (size_t)b * SCR_BATCH + (blk * SQ + q0) * 32 + (ln ^ ((ln >> 3) & 3)) * 8);
                }
                PROF((threadIdx.x & 127) == 0 && (!all3 || w == 2), 2);
                __syncwarp();
                if (lane == 0) mbar_arrive_n(DONE_BAR, all3 ? 1 : 3);
            }
        }
    } else {
        asm volatile("setmaxnreg.dec.sync.aligned.u32 32;");
        if (warp == 12) {
            nbar_sync(0, 512);
            uint32_t word = mbox[0];
            {
                uint32_t* dst = reinterpret_cast<uint32_t*>(sgen + OFF_TABLE);
                const uint32_t* src = reinterpret_cast<const uint32_t*>(P.table);
                for (int i = lane; i < NT_MAX / 2; i += 32) dst[i] = src[i];
            }
            __syncwarp();
            if (lane == 0) {
                uint32_t rr = ((word & 0x4007) == T_MHA || (word & 7) == T_FIN) ? 2 : 0, mbs = 1 | 4, wph = 0;
                mbar_wait(bar + 8 * B_SETUP, 0);
                const uint32_t base = mbox[8] * P.nt - gridDim.x;
                do {
                    uint32_t t, spins = 0;
                    while (!mbar_try(bar + 8 * B_WANT, wph)) {
                        if ((word & 7) == T_FIN) {
                            asm volatile("ld.relaxed.gpu.global.u32 %0, [%1];" : "=r"(t) : "l"(&g_task_ctr[0]) : "memory");
                            if (t - base >= P.nt) break;
                        }
                        if (++spins > (1u << 22)) __trap();
                    }
                    wph ^= 1;
                    asm volatile("atom.relaxed.gpu.global.add.u32 %0, [%1], 1;" : "=r"(t) : "l"(&g_task_ctr[0]) : "memory");
                    t -= base;
                    word = T_END;
                    if (t < P.nt) {
                        word = reinterpret_cast<const uint16_t*>(sgen + OFF_TABLE)[t];
                        if ((word & 0x4007) == T_MHA || (word & 7) == T_FIN) { word |= rr << 16; rr = wrap3(rr + 2); }
                    }
                    const uint32_t mbi = mbs & 3;
                    mbar_wait(bar + 8 * (B_MBEMPTY + mbi), mbs >> 2);
                    mbox[mbi] = word;
                    mbar_arrive(bar + 8 * (B_MBFULL + mbi));
                    mbs = (mbs + 1) & 7;
                } while (word != T_END);
            }
        } else if (warp == 13) {
            nbar_sync(0, 512);
            if (lane == 0) {
                const unsigned long long ticket = atomicAdd(&g_ticket[0], 1ull);
                const uint32_t e1 = (uint32_t)(ticket / gridDim.x) + 1;
                mbox[8] = e1 - 1;
                mbar_arrive(bar + 8 * B_SETUP);
                uint32_t mbs = 0, qeph = 7, tickets = 0;
                while (true) {
                    mbar_wait(bar + 8 * (B_MBFULL + (mbs & 3)), mbs >> 2);
                    const uint32_t word = mbox[mbs & 3];
                    mbar_arrive(bar + 8 * (B_MBEMPTY + (mbs & 3)));
                    const uint32_t grant = bar + 8 * (B_GRANT + (mbs & 3));
                    mbs = (mbs + 1) & 7;
                    const uint32_t type = word & 7, w = word >> 16;
                    if (type == T_END) break;
                    if (type == T_QP) {
                        mbar_arrive(grant);
                    } else if (type == T_OWN) {
                        const int f0 = ((word & 8) ? F_OFB : F_OFA) + ((word >> 4) & 7), nb = (word & 8) ? 28 : 8;
                        for (int k = 0; k < nb; k++) {
                            poll_flag(f0 + k * 8, 4 * e1);
                            tickets++;
                            asm volatile("st.release.cta.shared.u32 [%0], %1;" ::"r"(sb + OFF_MBOX + 36), "r"(tickets) : "memory");
                        }
                        if (word & 8) poll_flag(F_RFA + 6 * 8 + ((word >> 4) & 7), 2 * e1);
                        mbar_arrive(grant);
                    } else if (type != T_FIN) {
                        const int b = (word >> 4) & 31, h = (word >> 9) & 31, cnt = (type == T_GQA || (word & 0x4000)) ? 3 : 1;
                        if (word & 0x8000) { poll_flag(F_QF + ((h - HQ) >> 1) * 8 + (b >> 2), e1); fence_proxy_async_global(); }
                        for (int k = 0; k < cnt; k++) {
                            const uint32_t wi = w + k, f = bar + 8 * (B_QFULL_PV + wi);
                            mbar_wait(bar + 8 * (B_QEMPTY + wi), (qeph >> wi) & 1);
                            qeph ^= 1u << wi;
                            if (word & 0x8000) {
                                mbar_expect(f, 12288);
                                tma2d(sb + OFF_Q + wi * 8192, &P.maps[M_Q], 0, (b * (NH - HQ) + h - HQ) * 2 * SQ, f);
                                tma2d(sb + OFF_Q + 24576 + wi * 8192, &P.maps[M_Q], 0, (b * (NH - HQ) + h - HQ) * 2 * SQ + SQ, f);
                            } else mbar_arrive(f);
                        }
                        if (P.dbg & 8) {
                        } else if (type == T_GQA) {
                            if (h >= RSA) poll_flag(F_RFA + (h - RSA) * 8 + (b >> 2), 2 * e1);
                        } else if (h >= RSB) {
                            poll_flag(F_RFB + (h - RSB) * 8 + (b >> 2), 2 * e1);
                            if (((b + cnt - 1) >> 2) != (b >> 2)) poll_flag(F_RFB + (h - RSB) * 8 + (b >> 2) + 1, 2 * e1);
                        }
                        mbar_arrive(grant);
                    } else {
                        const int b = (word >> 4) & 31;
                        const uint32_t abit = 16u << ((word >> 10) & 1);
                        uint32_t todo = 15 | abit, spins = 0, k = 0;
                        bool qfree = false;
                        while (todo) {
                            uint32_t v;
                            asm volatile("ld.relaxed.gpu.global.u32 %0, [%1];" : "=r"(v) : "l"(&g_flags[(F_FB + b) * 8]) : "memory");
                            uint32_t rdy = (v - 63u * (e1 - 1)) & todo;
                            if (!qfree && (rdy & 15)) {
                                if ((rdy | abit) == (todo | abit)) for (int i = 0; i < 3; i++) mbar_wait(bar + 8 * (B_QEMPTY + i), (qeph >> i) & 1);
                                qfree = mbar_test(bar + 8 * B_QEMPTY, qeph & 1) && mbar_test(bar + 8 * (B_QEMPTY + 1), (qeph >> 1) & 1) &&
                                        mbar_test(bar + 8 * (B_QEMPTY + 2), (qeph >> 2) & 1);
                                if (!qfree) rdy &= abit;
                            }
                            if (rdy) {
                                todo ^= rdy;
                                asm volatile("fence.acquire.gpu;" ::: "memory");
                                fence_proxy_async_global();
#pragma unroll 1
                                for (int i = 0; i < 4; i++)
                                    if ((rdy >> i) & 1) {
                                        mbox[12 + k] = i;
                                        mbar_expect(bar + 8 * (B_FINA + k), 12288);
                                        tma2d(sb + OFF_Q + k * 12288, &P.maps[M_SQ], 0, (b * SCR_BLKS + SCR_B0 + ((28 + i) % RSB) * 4) * 6, bar + 8 * (B_FINA + k));
                                        k++;
                                    }
                                if (rdy & abit) mbar_arrive(grant);
                            } else if (++spins > (1u << 21)) __trap();
                        }
                        qeph ^= 7;
                    }
                }
            }
        } else if (warp == 14) {
            nbar_sync(0, 512);
            if (lane == 0) {
                uint32_t mbs = 0;
                while (true) {
                    const uint32_t mbi = mbs & 3;
                    mbar_wait(bar + 8 * (B_MBFULL + mbi), mbs >> 2);
                    const uint32_t word = mbox[mbi];
                    const uint32_t type = word & 7;
                    if (type == T_END) break;
                    mbar_wait(bar + 8 * (B_DONE + mbi), mbs >> 2);
                    if (type != T_FIN && !(type == T_OWN && !(word & 8))) {
                        if (!(P.dbg & 32)) {
                        fence_proxy_async_global();
                        asm volatile("fence.release.gpu;" ::: "memory");
                        }
                        if (type == T_QP) flag_add(F_QF + (((word >> 7) & 15) - HQ / 2) * 8 + ((word >> 4) & 7));
                        else if (type == T_GQA) flag_add(F_OFA + ((word >> 9) & 7) * 8 + ((word >> 6) & 7));
                        else if (type == T_OWN) { for (int k = 0; k < 4; k++) flag_add(F_FB + ((word >> 4) & 7) * 4 + k, 16u << ((word >> 7) & 1)); }
                        else {
                            const int b = (word >> 4) & 31, h = (word >> 9) & 31, cnt = (word & 0x4000) ? 3 : 1;
                            for (int k = 0; k < cnt; k++) flag_add(h >= 28 ? F_FB + b + k : F_OFB + h * 8 + ((b + k) >> 2), h >= 28 ? 1u << (h - 28) : 1u);
                        }
                    }
                    mbar_arrive(bar + 8 * (B_MBEMPTY + mbi));
                    mbs = (mbs + 1) & 7;
                }
            }
        } else {
            uint64_t pol;
            asm volatile("createpolicy.fractional.L2::evict_first.b64 %0, 1.0;" : "=l"(pol));
            uint32_t slot = 0, epar = 1, mbs = 0, tickets = 0;
            uint32_t word = __shfl_sync(0xffffffffu, (uint32_t)P.table[blockIdx.x], 0);
#define PTRACE(i) do {} while (0)
#define DST (sb + OFF_RING + slot * SLOT_BYTES)
#define ACQUIRE() mbar_wait(bar + 8 * (B_EMPTY + slot), epar)
#define ADVANCE() do { if (++slot == NSLOT) { slot = 0; epar ^= 1; } } while (0)
#define WANT() mbar_arrive(bar + 8 * B_WANT)
            uint32_t fset = 0, fpar = 0;
            bool first = true;
#define NOTE(set) do { fpar ^= 1u << ((set) * 5 + slot); fset = (fset & ~(3u << (2 * slot))) | ((set) << (2 * slot)); } while (0)
            nbar_sync(13, 512);
            while (true) {
                const uint32_t type = word & 7;
                if (type == T_END) break;
                const int b = (word >> 4) & 31, h = (word >> 9) & 31;
                if (type == T_MHA || type == T_GQA) {
                    const bool gqa = type == T_GQA, tri = (word & 0x4000) != 0;
                    if (!(word & 0x8000)) {
                        const uint32_t set = (gqa || tri) ? 0 : 1 + (word >> 16), fo = bar + 40 * set;
                        const uint32_t bytes = gqa ? 35840 : tri ? 34816 : 22528, aoff = gqa ? 32768 : 16384;
                        const CUtensorMap* mw = &P.maps[gqa ? M_WQA : M_WQB];
                        const CUtensorMap* mx = &P.maps[gqa ? M_XA : tri ? M_XB3 : M_XB1];
                        const int n = gqa ? 16 : 8, kstep = gqa ? 32 : 64, c2 = gqa ? h * 8 : h * 2;
#pragma unroll 1
                        for (int i = 0; i < n; i++) {
                            const uint32_t f = fo + 8 * slot, dst = DST;
                            ACQUIRE();
                            if (elect_one()) {
                                {
                                mbar_expect(f, bytes);
                                if ((EXPM & 8) && b >= (gqa ? 30 : 28)) tma3d_h(dst, mw, i * kstep, c2, f, pol);
                                else tma3d(dst, mw, i * kstep, c2, f);
                                tma3d(dst + aoff, mx, b * SQ, i, f);
                                }
                            }
                            NOTE(set);
                            ADVANCE();
                        }
                    }
                    const CUtensorMap* mk = &P.maps[gqa ? M_KA : M_KB];
                    const int row0 = (b * (gqa ? 8 : 32) + h) * (SK / 8), n = tri ? 24 : 8, want = gqa ? -1 : n - P.grab;
                    uint32_t cap2 = gqa ? P.capg : tri ? P.capt : h >= 28 ? (b >= P.bq ? P.capz : P.capq) : P.caps;
                    if (first && P.fmod) cap2 = P.flo + blockIdx.x % P.fmod;
                    first = false;
#pragma unroll 1
                    for (int i = 0; i < n; i++) {
                        const uint32_t u = tri ? tri_pos(i) : gqa ? i : (0x73652140u >> (4 * i)) & 7;
                        const uint32_t set = gqa ? 0 : tri ? 1 + (u >> 3) : 1 + wrap3((word >> 16) + 1 - (u >> 2));
                        const uint32_t f = bar + 8 * (5 * set + slot), dst = DST;
                        const int row = row0 + (u >> 3) * (32 * SK / 8) + ((u & 7) >> 1) * 16;
                        const uint32_t cap = (cap2 + (i & 1)) >> 1;
                        if (cap < NSLOT) {
                            const uint32_t ps = wrap5(slot + NSLOT - cap), pb = ((fset >> (2 * ps)) & 3) * 5 + ps;
                            mbar_wait(bar + 8 * pb, ((fpar >> pb) & 1) ^ 1);
                        }
                        ACQUIRE();
                        if (elect_one()) {
                            mbar_expect(f, 32768);
                            tma_stream(dst, mk + (u & 1), row, f, pol);
                            if (i == want) WANT();
                            PTRACE(i);
                        }
                        NOTE(set);
                        ADVANCE();
                    }
                    if (gqa) {
                        ACQUIRE();
                        if (elect_one()) WANT();
                    }
                } else if (type == T_QP) {
#pragma unroll 1
                    for (int i = 0; i < 16; i++) {
                        const uint32_t f = bar + 8 * (B_FULL_SH + slot), dst = DST;
                        ACQUIRE();
                        if (elect_one()) {
                            mbar_expect(f, 28672);
                            tma3d(dst, &P.maps[M_WQP], i * 32, ((word >> 7) & 15) * 4, f);
                            tma3d(dst + 16384, &P.maps[M_XP], (b & 7) * 192, i, f);
                            if (i == 14) WANT();
                        }
                        NOTE(0u);
                        ADVANCE();
                    }
                } else if (type == T_OWN) {
                    const uint32_t br = (word >> 3) & 1;
                    const int n = br ? 112 : 128, blk0 = br ? SCR_B0 : 0, blk1 = br ? SCR_BLKS : SCR_B0;
                    int blk = blk0;
#pragma unroll 1
                    for (int i = 0; i < n; i++) {
                        if ((i & (br ? 3 : 15)) == 0) {
                            tickets++;
                            uint32_t v, c = 0;
                            while (true) {
                                asm volatile("ld.acquire.cta.shared.u32 %0, [%1];" : "=r"(v) : "r"(sb + OFF_MBOX + 36) : "memory");
                                if (v >= tickets) break;
                                if (++c > (1u << 23)) __trap();
                                __nanosleep(32);
                            }
                            fence_proxy_async_global();
                        }
                        const uint32_t f = bar + 8 * (B_FULL_SH + slot), dst = DST;
                        ACQUIRE();
                        if (elect_one()) {
                            {
                            mbar_expect(f, 28672);
                            if ((EXPM & 2) && (b & 7) >= 6) tma5d_h(dst, &P.maps[M_WOA + br], 0, i * 4, ((word >> 7) & 1) * 4, f, pol);
                            else tma5d(dst, &P.maps[M_WOA + br], 0, i * 4, ((word >> 7) & 1) * 4, f);
                            if (EXPM & 1) tma3d_h(dst + 16384, &P.maps[M_SA], blk * 6, (b & 7) * 4, f, pol);
                            else tma3d(dst + 16384, &P.maps[M_SA], blk * 6, (b & 7) * 4, f);
                            }
                            if (i == n - 3) WANT();
                        }
                        if (++blk == blk1) blk = blk0;
                        NOTE(0u);
                        ADVANCE();
                    }
                } else {
#pragma unroll 1
                    for (int i = 0; i < 4; i++) {
                        const uint32_t f = bar + 8 * (B_FULL_PV + 5 * (word >> 16) + slot), dst = DST;
                        ACQUIRE();
                        if (elect_one()) {
                            mbar_expect(f, 32768);
                            tma5d(dst, &P.maps[M_WOF], (h & 3) * 128, 0, (28 + i) * 4, f);
                            tma5d(dst + 16384, &P.maps[M_WOF], (h & 3) * 128 + 64, 0, (28 + i) * 4, f);
                        }
                        NOTE(1 + (word >> 16));
                        ADVANCE();
                    }
                    mbar_wait(bar + 8 * (B_EMPTY + (slot == 0 ? NSLOT - 1 : slot - 1)), slot == 0 ? epar : epar ^ 1);
                    if (elect_one()) WANT();
                }
                if (elect_one()) mbar_arrive(bar + 8 * (B_MBEMPTY + (mbs & 3)));
                mbs = (mbs + 1) & 7;
                mbar_wait(bar + 8 * (B_MBFULL + (mbs & 3)), mbs >> 2);
                word = __shfl_sync(0xffffffffu, mbox[mbs & 3], 0);
            }
        }
    }
}

struct Knobs {
    float a0;
    float a1;
    float owna, ownb;
    float finlag;
    float single;
    float grab, s0, qp0, qpd, capt, caps, capq, capg, flo, fmod, bq, capz, hm, dbg, grid, pkv, pw;
};
Knobs KN = {0.5f, 24.0f, 5.f, 6.5f, 4.0f, 24.f, 3.f, 2.f, 18.f, 0.2f, 4.f, 3.f, 2.5f, 3.f, 3.f, 8.f, 32.f, 5.f, 1.f, 0.f, 0.f, 2.f, 2.f};

typedef CUresult (*EncodeFn)(CUtensorMap*, CUtensorMapDataType, cuuint32_t, void*, const cuuint64_t*, const cuuint64_t*,
                             const cuuint32_t*, const cuuint32_t*, CUtensorMapInterleave, CUtensorMapSwizzle,
                             CUtensorMapL2promotion, CUtensorMapFloatOOBfill);

void enc(EncodeFn fn, CUtensorMap* m, const void* ptr, int rank, uint64_t d0, uint64_t d1, uint64_t d2, uint64_t s1, uint64_t s2,
         uint32_t b0, uint32_t b1, uint32_t b2, CUtensorMapSwizzle sw) {
    cuuint64_t dims[3] = {d0, d1, d2};
    cuuint64_t strides[2] = {s1, s2};
    cuuint32_t box[3] = {b0, b1, b2};
    cuuint32_t es[3] = {1, 1, 1};
    fn(m, CU_TENSOR_MAP_DATA_TYPE_BFLOAT16, rank, const_cast<void*>(ptr), dims, strides, box, es, CU_TENSOR_MAP_INTERLEAVE_NONE, sw,
       (CUtensorMapL2promotion)(int)KN.pw, CU_TENSOR_MAP_FLOAT_OOB_FILL_NONE);
}

int build_table(uint16_t* table) {
    static float key[NT_MAX];
    static uint16_t word[NT_MAX];
    static int idx[NT_MAX];
    int n = 0;
    for (int h = 0; h < 28; h++)
        for (int b = 0; b < 32;) {
            const bool tri = h < HQ && h + b / 32.f < KN.single && h + b / 32.f >= KN.s0 && b + 3 <= 32 && !(b == 15);
            key[n] = h + b / 32.f;
            word[n++] = (uint16_t)(T_MHA | 8 | (b << 4) | (h << 9) | (tri ? 0x4000 : 0) | (h >= HQ ? 0x8000 : 0));
            b += tri ? 3 : 1;
        }
    for (int j = HQ / 2; j < 16; j++)
        for (int g = 0; g < 8; g++) {
            key[n] = KN.qp0 + ((j - HQ / 2) * 8 + g) * KN.qpd;
            word[n++] = (uint16_t)(T_QP | (g << 4) | (j << 7));
        }
    for (int b = 0; b < 32; b++)
        for (int q = 0; q < 4; q++) {
            key[n] = 28.f + (1.f - KN.hm) * (b * 4 + q) / 32.f + KN.hm * (q * 32 + b) / 32.f;
            word[n++] = (uint16_t)(T_MHA | 8 | (b << 4) | ((28 + q) << 9) | (28 + q >= HQ ? 0x8000 : 0));
            key[n] = 28.f + (b * 4 + 4 + q) / 32.f + KN.finlag;
            word[n++] = (uint16_t)(T_FIN | 8 | (b << 4) | (q << 9));
        }
    const float da = (KN.a1 - KN.a0) / 256.f;
    for (int r = 0; r < 8; r++)
        for (int g = 0; g < 8; g++) {
            const float ka = KN.a0 + (r * 32 + g * 4) * da;
            for (int i = 0; i < 4; i++) {
                key[n] = ka + i * da + 0.001f;
                word[n++] = (uint16_t)(T_GQA | ((g * 4 + i) << 4) | (r << 9));
            }
        }
    for (int i = 0; i < 32; i++) {
        key[n] = (i < 16 ? KN.ownb : KN.owna) + i * 0.001f;
        word[n++] = (uint16_t)(T_OWN | ((1 - (i >> 4)) << 3) | (((i >> 1) & 7) << 4) | ((i & 1) << 7));
    }
    {
        const int dbg = (int)KN.dbg;
        int m = 0;
        for (int i = 0; i < n; i++) {
            const int ty = word[i] & 7;
            if ((ty == T_GQA && (dbg & 2)) || (ty == T_MHA && (dbg & 4)) || ((ty == T_OWN || ty == T_FIN) && (dbg & 8))) continue;
            key[m] = key[i]; word[m++] = word[i];
        }
        n = m;
    }
    for (int i = 0; i < n; i++) idx[i] = i;
    for (int i = 1; i < n; i++) {
        const int v = idx[i];
        int j = i - 1;
        while (j >= 0 && key[idx[j]] > key[v]) { idx[j + 1] = idx[j]; j--; }
        idx[j + 1] = v;
    }
    for (int i = 0; i < n; i++) table[i] = word[idx[i]];
    for (int i = n; i < NT_MAX; i++) table[i] = T_END;
    return n;
}

}

extern "C" void kernel_launch(void* const* d_in, const int* in_sizes, int n_in, void* d_out, int out_size) {
    (void)in_sizes; (void)n_in; (void)out_size;
    static Params P;
    static int nsm = 0;
    void* fnp = nullptr;
    cudaDriverEntryPointQueryResult qr;
    cudaGetDriverEntryPoint("cuTensorMapEncodeTiled", &fnp, cudaEnableDefault, &qr);
    EncodeFn fn = (EncodeFn)fnp;
    void* scr = nullptr;
    void* qs = nullptr;
    cudaGetSymbolAddress(&scr, g_scr);
    cudaGetSymbolAddress(&qs, g_q);
    const CUtensorMapSwizzle S128 = CU_TENSOR_MAP_SWIZZLE_128B, S64 = CU_TENSOR_MAP_SWIZZLE_64B;
    for (int i = 0; i < 4; i++) {
        cuuint64_t dims[4] = {64, 8, 2, (cuuint64_t)NB * (i < 2 ? 8 : NH) * (SK / 8)}, strides[3] = {256, 128, 2048};
        cuuint32_t box[4] = {64, 8, 2, 16}, es[4] = {1, 1, 1, 1};
        fn(&P.maps[M_KA + i], CU_TENSOR_MAP_DATA_TYPE_BFLOAT16, 4, d_in[i < 2 ? 1 + i : 4 + i], dims, strides, box, es, CU_TENSOR_MAP_INTERLEAVE_NONE, S128,
           (CUtensorMapL2promotion)(int)KN.pkv, CU_TENSOR_MAP_FLOAT_OOB_FILL_NONE);
    }
    enc(fn, &P.maps[M_XA], d_in[0], 3, 32, NTOK, 16, DM * 2, 64, 32, 48, 1, S64);
    enc(fn, &P.maps[M_XB3], d_in[5], 3, 64, NTOK, 8, DM * 2, 128, 64, 144, 1, S128);
    enc(fn, &P.maps[M_XB1], d_in[5], 3, 64, NTOK, 8, DM * 2, 128, 64, 48, 1, S128);
    enc(fn, &P.maps[M_WQA], d_in[3], 3, 64, DM, 64, NH * DH * 2, 128, 64, 32, 8, S128);
    enc(fn, &P.maps[M_WQB], d_in[8], 3, 64, DM, 64, NH * DH * 2, 128, 64, 64, 2, S128);
    for (int i = 0; i < 3; i++) {
        const bool fin = i == 2;
        cuuint64_t dims[5] = {fin ? 512u : 64u, 2, fin ? 4u : 512u, 4, fin ? 128u : 8u};
        cuuint64_t strides[4] = {1024, 8 * 1024, 2 * 1024, fin ? 32u * 1024u : 128u};
        cuuint32_t box[5] = {64, 2, 4, 4, 4}, es[5] = {1, 1, 1, 1, 1};
        fn(&P.maps[M_WOA + i], CU_TENSOR_MAP_DATA_TYPE_BFLOAT16, 5, d_in[i ? 9 : 4], dims, strides, box, es, CU_TENSOR_MAP_INTERLEAVE_NONE, S128,
           (CUtensorMapL2promotion)(int)KN.pw, CU_TENSOR_MAP_FLOAT_OOB_FILL_NONE);
    }
    enc(fn, &P.maps[M_SA], scr, 3, 256, SCR_BLKS * 6, NB, 512, SCR_BATCH * 2, 256, 6, 4, CU_TENSOR_MAP_SWIZZLE_NONE);
    enc(fn, &P.maps[M_SQ], scr, 2, 256, NB * SCR_BLKS * 6, 1, 512, 0, 256, 24, 1, CU_TENSOR_MAP_SWIZZLE_NONE);
    enc(fn, &P.maps[M_WQP], d_in[8], 3, 64, DM, 64, NH * DH * 2, 128, 64, 32, 4, S128);
    enc(fn, &P.maps[M_XP], d_in[5], 3, 32, NTOK, 16, DM * 2, 64, 32, 192, 1, S64);
    enc(fn, &P.maps[M_Q], qs, 2, 64, NB * (NH - HQ) * 2 * SQ + 64, 1, 128, 0, 64, SQ, 1, S128);
    P.out = (__nv_bfloat16*)d_out;
    P.nt = (uint32_t)build_table(P.table);
    P.grab = (int)KN.grab; P.flo = (int)KN.flo; P.fmod = (int)KN.fmod; P.bq = (int)KN.bq; P.capz = (int)(2 * KN.capz); P.capt = (int)(2 * KN.capt); P.caps = (int)(2 * KN.caps); P.capq = (int)(2 * KN.capq); P.capg = (int)(2 * KN.capg); P.dbg = (int)KN.dbg;
    if (nsm == 0) {
        int dev = 0;
        cudaGetDevice(&dev);
        cudaDeviceGetAttribute(&nsm, cudaDevAttrMultiProcessorCount, dev);
        cudaFuncSetAttribute(fused_attn_kernel, cudaFuncAttributeMaxDynamicSharedMemorySize, SMEM_BYTES);
    }
    fused_attn_kernel<<<KN.grid > 0 ? (int)KN.grid : nsm, 512, SMEM_BYTES>>>(P);
}
```
